```python
import torch

def _softmax(x, axis=-1):
    return torch.softmax(x, dim=axis)
def _gelu(x):
    return torch.nn.functional.gelu(x, approximate="tanh")
def _silu(x):
    return torch.nn.functional.silu(x)
def _sigmoid(x):
    return torch.sigmoid(x)
def _layernorm(x, axis=-1, eps=1e-5):
    m = x.mean(dim=axis, keepdim=True)
    v = x.var(dim=axis, keepdim=True, unbiased=False)
    return (x - m) / torch.sqrt(v + eps)
def _scatter_add(tgt, idx, src, axis=0):
    return tgt.clone().index_add_(axis, idx, src)
def _segment_sum(src, seg, n):
    out = torch.zeros((n,) + src.shape[1:], dtype=src.dtype)
    return out.index_add_(0, seg, src)
def _pad(x, pw):
    flat = tuple(v for pair in reversed(pw) for v in pair)
    return torch.nn.functional.pad(x, flat)

kernel_name = 'sequential_preLN__sliding_local_dilated__swiglu_ffn__prompt'

def setup_inputs():

    _w = (lambda a: (lambda t: t.to(torch.bfloat16) if t.is_floating_point() else t)(torch.as_tensor(a)))
    def _A_setup():
        B, S, D = 1, 2048, 512
        return {
            "x": _w((lambda *s: torch.randn(*s, dtype=torch.bfloat16) * 0.05)(B, S, D)),
            "wqkv": _w((lambda *s: torch.randn(*s, dtype=torch.bfloat16) * 0.05)(D, 3 * D)),
            "wo": _w((lambda *s: torch.randn(*s, dtype=torch.bfloat16) * 0.05)(D, D)),
        }
    _A_in = _A_setup()

    def _B_setup():
        B, S, D, F = 1, 2048, 512, 1792
        return {
            "x": _w((lambda *s: torch.randn(*s, dtype=torch.bfloat16) * 0.05)(B, S, D)),
            "w_gate": _w((lambda *s: torch.randn(*s, dtype=torch.bfloat16) * 0.05)(D, F)),
            "w_up": _w((lambda *s: torch.randn(*s, dtype=torch.bfloat16) * 0.05)(D, F)),
            "w_down": _w((lambda *s: torch.randn(*s, dtype=torch.bfloat16) * 0.05)(F, D)),
        }
    _B_in = _B_setup()

    return {
        "A_x": _A_in["x"],
        "A_wqkv": _A_in["wqkv"],
        "A_wo": _A_in["wo"],
        "B_x": _B_in["x"],
        "B_w_gate": _B_in["w_gate"],
        "B_w_up": _B_in["w_up"],
        "B_w_down": _B_in["w_down"],
    }

def reference(A_x, A_wqkv, A_wo, B_x, B_w_gate, B_w_up, B_w_down):
    def _A_ref(x, wqkv, wo):
        B, S, D = x.shape
        H = 32; Dh = D // H
        W, dil = 8, 2
        qkv = (lambda x, *d: x.permute(*d))((x @ wqkv).reshape(B, S, 3, H, Dh), 2, 0, 3, 1, 4)
        q, k, v = qkv[0], qkv[1], qkv[2]
        scale = Dh ** -0.5
        pos = torch.arange(S)
        off = torch.arange(W) * dil
        idx = pos[:, None] - off[None, :]
        mask = idx >= 0
        idx_c = torch.where(mask, idx, 0).reshape(-1)
        kg = k[:, :, idx_c, :].reshape(B, H, S, W, Dh)
        vg = v[:, :, idx_c, :].reshape(B, H, S, W, Dh)
        logits = torch.einsum("bhsd,bhswd->bhsw", q, kg) * scale
        logits = torch.where(mask[None, None, :, :], logits, -1e9)
        attn = _softmax(logits, axis=-1)
        o = torch.einsum("bhsw,bhswd->bhsd", attn, vg)
        return (lambda x, *d: x.permute(*d))(o, 0, 2, 1, 3).reshape(B, S, D) @ wo

    def _B_ref(x, w_gate, w_up, w_down):
        g = _silu(x @ w_gate)
        u = x @ w_up
        return (g * u) @ w_down

    x = A_x
    h = x + _A_ref(_layernorm(x, axis=-1), A_wqkv, A_wo)
    h2 = h + _B_ref(_layernorm(h, axis=-1), B_w_gate, B_w_up, B_w_down)
    return h2
```

```cpp
#include <cuda_runtime.h>
#include <cuda_bf16.h>
#include <cuda.h>
#include <stdint.h>

typedef __nv_bfloat16 bf16;

constexpr int S_ = 2048, D_ = 512, F_ = 1792;

__device__ __align__(1024) bf16 g_o[S_ * D_];
__device__ __align__(1024) bf16 g_h[S_ * D_];
__device__ __align__(1024) bf16 g_act[S_ * F_];

#define DBG(k,i)
__device__ __forceinline__ uint32_t smem_u32(const void* p) { return (uint32_t)__cvta_generic_to_shared(p); }
__device__ __forceinline__ void mbar_init(uint32_t bar, uint32_t cnt) {
  asm volatile("mbarrier.init.shared::cta.b64 [%0], %1;" ::"r"(bar), "r"(cnt));
}
__device__ __forceinline__ void mbar_expect_tx(uint32_t bar, uint32_t bytes) {
  asm volatile("mbarrier.arrive.expect_tx.shared::cta.b64 _, [%0], %1;" ::"r"(bar), "r"(bytes) : "memory");
}
__device__ __forceinline__ void mbar_arrive(uint32_t bar) {
  asm volatile("mbarrier.arrive.shared::cta.b64 _, [%0];" ::"r"(bar) : "memory");
}
__device__ __forceinline__ void mbar_arrive_cluster(uint32_t bar_cluster_addr) {
  asm volatile("mbarrier.arrive.shared::cluster.b64 _, [%0];" ::"r"(bar_cluster_addr) : "memory");
}
__device__ __forceinline__ bool mbar_try(uint32_t bar, uint32_t parity) {
  uint32_t ok;
  asm volatile("{\n.reg .pred p;\nmbarrier.try_wait.parity.shared::cta.b64 p, [%1], %2;\nselp.u32 %0, 1, 0, p;\n}" : "=r"(ok) : "r"(bar), "r"(parity) : "memory");
  return ok != 0;
}
__device__ __forceinline__ bool mbar_try_cluster(uint32_t bar, uint32_t parity) {
  uint32_t ok;
  asm volatile("{\n.reg .pred p;\nmbarrier.try_wait.parity.acquire.cluster.shared::cta.b64 p, [%1], %2;\nselp.u32 %0, 1, 0, p;\n}" : "=r"(ok) : "r"(bar), "r"(parity) : "memory");
  return ok != 0;
}
__device__ __forceinline__ void mbar_wait(uint32_t bar, uint32_t parity) {
  if (mbar_try(bar, parity)) return;
  for (uint32_t it = 0; !mbar_try(bar, parity); it++)
    if (it > (1u << 22)) __trap();
}
__device__ __forceinline__ void mbar_wait_cluster(uint32_t bar, uint32_t parity) {
  if (mbar_try_cluster(bar, parity)) return;
  for (uint32_t it = 0; !mbar_try_cluster(bar, parity); it++)
    if (it > (1u << 22)) __trap();
}
__device__ __forceinline__ void tma_2d(uint32_t dst, const CUtensorMap* map, int c0, int c1, uint32_t bar) {
  asm volatile(
      "cp.async.bulk.tensor.2d.shared::cluster.global.mbarrier::complete_tx::bytes [%0], [%1, {%3, %4}], [%2];" ::"r"(dst),
      "l"(map), "r"(bar), "r"(c0), "r"(c1)
      : "memory");
}
__device__ __forceinline__ void tma_2d_mc(uint32_t dst, const CUtensorMap* map, int c0, int c1, uint32_t bar, uint16_t mask) {
  asm volatile(
      "cp.async.bulk.tensor.2d.shared::cluster.global.mbarrier::complete_tx::bytes.multicast::cluster [%0], [%1, {%3, %4}], [%2], %5;" ::"r"(dst),
      "l"(map), "r"(bar), "r"(c0), "r"(c1), "h"(mask)
      : "memory");
}
__device__ __forceinline__ void tma_3d(uint32_t dst, const CUtensorMap* map, int c0, int c1, int c2, uint32_t bar) {
  asm volatile(
      "cp.async.bulk.tensor.3d.shared::cluster.global.mbarrier::complete_tx::bytes [%0], [%1, {%3, %4, %5}], [%2];" ::"r"(dst),
      "l"(map), "r"(bar), "r"(c0), "r"(c1), "r"(c2)
      : "memory");
}
__device__ __forceinline__ void tma_3d_mc(uint32_t dst, const CUtensorMap* map, int c0, int c1, int c2, uint32_t bar, uint16_t mask) {
  asm volatile(
      "cp.async.bulk.tensor.3d.shared::cluster.global.mbarrier::complete_tx::bytes.multicast::cluster [%0], [%1, {%3, %4, %5}], [%2], %6;" ::"r"(dst),
      "l"(map), "r"(bar), "r"(c0), "r"(c1), "r"(c2), "h"(mask)
      : "memory");
}
__device__ __forceinline__ void fence_barrier_init() { asm volatile("fence.mbarrier_init.release.cluster;" ::: "memory"); }
__device__ __forceinline__ void fence_proxy_async() { asm volatile("fence.proxy.async.shared::cta;" ::: "memory"); }
__device__ __forceinline__ void named_bar_sync(int id, int n) { asm volatile("bar.sync %0, %1;" ::"r"(id), "r"(n) : "memory"); }
__device__ __forceinline__ void wgmma_fence() { asm volatile("wgmma.fence.sync.aligned;" ::: "memory"); }
__device__ __forceinline__ void wgmma_commit() { asm volatile("wgmma.commit_group.sync.aligned;" ::: "memory"); }
template <int N>
__device__ __forceinline__ void wgmma_wait() { asm volatile("wgmma.wait_group.sync.aligned %0;" ::"n"(N) : "memory"); }
__device__ __forceinline__ void cluster_arrive() { asm volatile("barrier.cluster.arrive.release.aligned;" ::: "memory"); }
__device__ __forceinline__ void cluster_arrive_relaxed() { asm volatile("barrier.cluster.arrive.relaxed.aligned;" ::: "memory"); }
__device__ __forceinline__ void cluster_wait() { asm volatile("barrier.cluster.wait.acquire.aligned;" ::: "memory"); }
__device__ __forceinline__ uint32_t mapa(uint32_t addr, uint32_t rank) {
  uint32_t r;
  asm volatile("mapa.shared::cluster.u32 %0, %1, %2;" : "=r"(r) : "r"(addr), "r"(rank));
  return r;
}
__device__ __forceinline__ void pdl_launch_dependents() { asm volatile("griddepcontrol.launch_dependents;" ::: "memory"); }
__device__ __forceinline__ void pdl_wait() { asm volatile("griddepcontrol.wait;" ::: "memory"); }

__device__ __forceinline__ uint64_t make_desc(uint32_t addr, uint32_t lbo, uint32_t sbo) {
  uint64_t d = 0;
  d |= (uint64_t)((addr & 0x3FFFF) >> 4);
  d |= (uint64_t)((lbo & 0x3FFFF) >> 4) << 16;
  d |= (uint64_t)((sbo & 0x3FFFF) >> 4) << 32;
  d |= (uint64_t)1 << 62;
  return d;
}

__device__ __forceinline__ uint64_t make_desc_ns(uint32_t addr, uint32_t lbo, uint32_t sbo) {
  uint64_t d = 0;
  d |= (uint64_t)((addr & 0x3FFFF) >> 4);
  d |= (uint64_t)((lbo & 0x3FFFF) >> 4) << 16;
  d |= (uint64_t)((sbo & 0x3FFFF) >> 4) << 32;
  return d;
}
__device__ __forceinline__ void bulk_load(uint32_t dst, const void* src, uint32_t bytes, uint32_t bar) {
  asm volatile("cp.async.bulk.shared::cluster.global.mbarrier::complete_tx::bytes [%0], [%1], %2, [%3];" ::"r"(dst), "l"(src), "r"(bytes), "r"(bar) : "memory");
}
__device__ __forceinline__ void bulk_load_mc(uint32_t dst, const void* src, uint32_t bytes, uint32_t bar, uint16_t mask) {
  asm volatile("cp.async.bulk.shared::cluster.global.mbarrier::complete_tx::bytes.multicast::cluster [%0], [%1], %2, [%3], %4;" ::"r"(dst), "l"(src), "r"(bytes), "r"(bar), "h"(mask) : "memory");
}

template<int TA, int TB>
__device__ __forceinline__ void wgmma_n64(float (&d)[32], uint64_t da, uint64_t db, int scale_d) {
  asm volatile("{\n.reg .pred p;\nsetp.ne.b32 p, %34, 0;\n"
    "wgmma.mma_async.sync.aligned.m64n64k16.f32.bf16.bf16 {%0, %1, %2, %3, %4, %5, %6, %7, %8, %9, %10, %11, %12, %13, %14, %15, %16, %17, %18, %19, %20, %21, %22, %23, %24, %25, %26, %27, %28, %29, %30, %31}, %32, %33, p, 1, 1, %35, %36;\n}\n"
    : "+f"(d[0]), "+f"(d[1]), "+f"(d[2]), "+f"(d[3]), "+f"(d[4]), "+f"(d[5]), "+f"(d[6]), "+f"(d[7]), "+f"(d[8]), "+f"(d[9]), "+f"(d[10]), "+f"(d[11]), "+f"(d[12]), "+f"(d[13]), "+f"(d[14]), "+f"(d[15]), "+f"(d[16]), "+f"(d[17]), "+f"(d[18]), "+f"(d[19]), "+f"(d[20]), "+f"(d[21]), "+f"(d[22]), "+f"(d[23]), "+f"(d[24]), "+f"(d[25]), "+f"(d[26]), "+f"(d[27]), "+f"(d[28]), "+f"(d[29]), "+f"(d[30]), "+f"(d[31])
    : "l"(da), "l"(db), "r"(scale_d), "n"(TA), "n"(TB));
}

template<int TA, int TB>
__device__ __forceinline__ void wgmma_n72(float (&d)[36], uint64_t da, uint64_t db, int scale_d) {
  asm volatile("{\n.reg .pred p;\nsetp.ne.b32 p, %38, 0;\n"
    "wgmma.mma_async.sync.aligned.m64n72k16.f32.bf16.bf16 {%0, %1, %2, %3, %4, %5, %6, %7, %8, %9, %10, %11, %12, %13, %14, %15, %16, %17, %18, %19, %20, %21, %22, %23, %24, %25, %26, %27, %28, %29, %30, %31, %32, %33, %34, %35}, %36, %37, p, 1, 1, %39, %40;\n}\n"
    : "+f"(d[0]), "+f"(d[1]), "+f"(d[2]), "+f"(d[3]), "+f"(d[4]), "+f"(d[5]), "+f"(d[6]), "+f"(d[7]), "+f"(d[8]), "+f"(d[9]), "+f"(d[10]), "+f"(d[11]), "+f"(d[12]), "+f"(d[13]), "+f"(d[14]), "+f"(d[15]), "+f"(d[16]), "+f"(d[17]), "+f"(d[18]), "+f"(d[19]), "+f"(d[20]), "+f"(d[21]), "+f"(d[22]), "+f"(d[23]), "+f"(d[24]), "+f"(d[25]), "+f"(d[26]), "+f"(d[27]), "+f"(d[28]), "+f"(d[29]), "+f"(d[30]), "+f"(d[31]), "+f"(d[32]), "+f"(d[33]), "+f"(d[34]), "+f"(d[35])
    : "l"(da), "l"(db), "r"(scale_d), "n"(TA), "n"(TB));
}

template<int TA, int TB>
__device__ __forceinline__ void wgmma_n80(float (&d)[40], uint64_t da, uint64_t db, int scale_d) {
  asm volatile("{\n.reg .pred p;\nsetp.ne.b32 p, %42, 0;\n"
    "wgmma.mma_async.sync.aligned.m64n80k16.f32.bf16.bf16 {%0, %1, %2, %3, %4, %5, %6, %7, %8, %9, %10, %11, %12, %13, %14, %15, %16, %17, %18, %19, %20, %21, %22, %23, %24, %25, %26, %27, %28, %29, %30, %31, %32, %33, %34, %35, %36, %37, %38, %39}, %40, %41, p, 1, 1, %43, %44;\n}\n"
    : "+f"(d[0]), "+f"(d[1]), "+f"(d[2]), "+f"(d[3]), "+f"(d[4]), "+f"(d[5]), "+f"(d[6]), "+f"(d[7]), "+f"(d[8]), "+f"(d[9]), "+f"(d[10]), "+f"(d[11]), "+f"(d[12]), "+f"(d[13]), "+f"(d[14]), "+f"(d[15]), "+f"(d[16]), "+f"(d[17]), "+f"(d[18]), "+f"(d[19]), "+f"(d[20]), "+f"(d[21]), "+f"(d[22]), "+f"(d[23]), "+f"(d[24]), "+f"(d[25]), "+f"(d[26]), "+f"(d[27]), "+f"(d[28]), "+f"(d[29]), "+f"(d[30]), "+f"(d[31]), "+f"(d[32]), "+f"(d[33]), "+f"(d[34]), "+f"(d[35]), "+f"(d[36]), "+f"(d[37]), "+f"(d[38]), "+f"(d[39])
    : "l"(da), "l"(db), "r"(scale_d), "n"(TA), "n"(TB));
}

template<int TA, int TB>
__device__ __forceinline__ void wgmma_n128(float (&d)[64], uint64_t da, uint64_t db, int scale_d) {
  asm volatile("{\n.reg .pred p;\nsetp.ne.b32 p, %66, 0;\n"
    "wgmma.mma_async.sync.aligned.m64n128k16.f32.bf16.bf16 {%0, %1, %2, %3, %4, %5, %6, %7, %8, %9, %10, %11, %12, %13, %14, %15, %16, %17, %18, %19, %20, %21, %22, %23, %24, %25, %26, %27, %28, %29, %30, %31, %32, %33, %34, %35, %36, %37, %38, %39, %40, %41, %42, %43, %44, %45, %46, %47, %48, %49, %50, %51, %52, %53, %54, %55, %56, %57, %58, %59, %60, %61, %62, %63}, %64, %65, p, 1, 1, %67, %68;\n}\n"
    : "+f"(d[0]), "+f"(d[1]), "+f"(d[2]), "+f"(d[3]), "+f"(d[4]), "+f"(d[5]), "+f"(d[6]), "+f"(d[7]), "+f"(d[8]), "+f"(d[9]), "+f"(d[10]), "+f"(d[11]), "+f"(d[12]), "+f"(d[13]), "+f"(d[14]), "+f"(d[15]), "+f"(d[16]), "+f"(d[17]), "+f"(d[18]), "+f"(d[19]), "+f"(d[20]), "+f"(d[21]), "+f"(d[22]), "+f"(d[23]), "+f"(d[24]), "+f"(d[25]), "+f"(d[26]), "+f"(d[27]), "+f"(d[28]), "+f"(d[29]), "+f"(d[30]), "+f"(d[31]), "+f"(d[32]), "+f"(d[33]), "+f"(d[34]), "+f"(d[35]), "+f"(d[36]), "+f"(d[37]), "+f"(d[38]), "+f"(d[39]), "+f"(d[40]), "+f"(d[41]), "+f"(d[42]), "+f"(d[43]), "+f"(d[44]), "+f"(d[45]), "+f"(d[46]), "+f"(d[47]), "+f"(d[48]), "+f"(d[49]), "+f"(d[50]), "+f"(d[51]), "+f"(d[52]), "+f"(d[53]), "+f"(d[54]), "+f"(d[55]), "+f"(d[56]), "+f"(d[57]), "+f"(d[58]), "+f"(d[59]), "+f"(d[60]), "+f"(d[61]), "+f"(d[62]), "+f"(d[63])
    : "l"(da), "l"(db), "r"(scale_d), "n"(TA), "n"(TB));
}

template<int TA, int TB>
__device__ __forceinline__ void wgmma_n136(float (&d)[68], uint64_t da, uint64_t db, int scale_d) {
  asm volatile("{\n.reg .pred p;\nsetp.ne.b32 p, %70, 0;\n"
    "wgmma.mma_async.sync.aligned.m64n136k16.f32.bf16.bf16 {%0, %1, %2, %3, %4, %5, %6, %7, %8, %9, %10, %11, %12, %13, %14, %15, %16, %17, %18, %19, %20, %21, %22, %23, %24, %25, %26, %27, %28, %29, %30, %31, %32, %33, %34, %35, %36, %37, %38, %39, %40, %41, %42, %43, %44, %45, %46, %47, %48, %49, %50, %51, %52, %53, %54, %55, %56, %57, %58, %59, %60, %61, %62, %63, %64, %65, %66, %67}, %68, %69, p, 1, 1, %71, %72;\n}\n"
    : "+f"(d[0]), "+f"(d[1]), "+f"(d[2]), "+f"(d[3]), "+f"(d[4]), "+f"(d[5]), "+f"(d[6]), "+f"(d[7]), "+f"(d[8]), "+f"(d[9]), "+f"(d[10]), "+f"(d[11]), "+f"(d[12]), "+f"(d[13]), "+f"(d[14]), "+f"(d[15]), "+f"(d[16]), "+f"(d[17]), "+f"(d[18]), "+f"(d[19]), "+f"(d[20]), "+f"(d[21]), "+f"(d[22]), "+f"(d[23]), "+f"(d[24]), "+f"(d[25]), "+f"(d[26]), "+f"(d[27]), "+f"(d[28]), "+f"(d[29]), "+f"(d[30]), "+f"(d[31]), "+f"(d[32]), "+f"(d[33]), "+f"(d[34]), "+f"(d[35]), "+f"(d[36]), "+f"(d[37]), "+f"(d[38]), "+f"(d[39]), "+f"(d[40]), "+f"(d[41]), "+f"(d[42]), "+f"(d[43]), "+f"(d[44]), "+f"(d[45]), "+f"(d[46]), "+f"(d[47]), "+f"(d[48]), "+f"(d[49]), "+f"(d[50]), "+f"(d[51]), "+f"(d[52]), "+f"(d[53]), "+f"(d[54]), "+f"(d[55]), "+f"(d[56]), "+f"(d[57]), "+f"(d[58]), "+f"(d[59]), "+f"(d[60]), "+f"(d[61]), "+f"(d[62]), "+f"(d[63]), "+f"(d[64]), "+f"(d[65]), "+f"(d[66]), "+f"(d[67])
    : "l"(da), "l"(db), "r"(scale_d), "n"(TA), "n"(TB));
}

template<int TA, int TB>
__device__ __forceinline__ void wgmma_n152(float (&d)[76], uint64_t da, uint64_t db, int scale_d) {
  asm volatile("{\n.reg .pred p;\nsetp.ne.b32 p, %78, 0;\n"
    "wgmma.mma_async.sync.aligned.m64n152k16.f32.bf16.bf16 {%0, %1, %2, %3, %4, %5, %6, %7, %8, %9, %10, %11, %12, %13, %14, %15, %16, %17, %18, %19, %20, %21, %22, %23, %24, %25, %26, %27, %28, %29, %30, %31, %32, %33, %34, %35, %36, %37, %38, %39, %40, %41, %42, %43, %44, %45, %46, %47, %48, %49, %50, %51, %52, %53, %54, %55, %56, %57, %58, %59, %60, %61, %62, %63, %64, %65, %66, %67, %68, %69, %70, %71, %72, %73, %74, %75}, %76, %77, p, 1, 1, %79, %80;\n}\n"
    : "+f"(d[0]), "+f"(d[1]), "+f"(d[2]), "+f"(d[3]), "+f"(d[4]), "+f"(d[5]), "+f"(d[6]), "+f"(d[7]), "+f"(d[8]), "+f"(d[9]), "+f"(d[10]), "+f"(d[11]), "+f"(d[12]), "+f"(d[13]), "+f"(d[14]), "+f"(d[15]), "+f"(d[16]), "+f"(d[17]), "+f"(d[18]), "+f"(d[19]), "+f"(d[20]), "+f"(d[21]), "+f"(d[22]), "+f"(d[23]), "+f"(d[24]), "+f"(d[25]), "+f"(d[26]), "+f"(d[27]), "+f"(d[28]), "+f"(d[29]), "+f"(d[30]), "+f"(d[31]), "+f"(d[32]), "+f"(d[33]), "+f"(d[34]), "+f"(d[35]), "+f"(d[36]), "+f"(d[37]), "+f"(d[38]), "+f"(d[39]), "+f"(d[40]), "+f"(d[41]), "+f"(d[42]), "+f"(d[43]), "+f"(d[44]), "+f"(d[45]), "+f"(d[46]), "+f"(d[47]), "+f"(d[48]), "+f"(d[49]), "+f"(d[50]), "+f"(d[51]), "+f"(d[52]), "+f"(d[53]), "+f"(d[54]), "+f"(d[55]), "+f"(d[56]), "+f"(d[57]), "+f"(d[58]), "+f"(d[59]), "+f"(d[60]), "+f"(d[61]), "+f"(d[62]), "+f"(d[63]), "+f"(d[64]), "+f"(d[65]), "+f"(d[66]), "+f"(d[67]), "+f"(d[68]), "+f"(d[69]), "+f"(d[70]), "+f"(d[71]), "+f"(d[72]), "+f"(d[73]), "+f"(d[74]), "+f"(d[75])
    : "l"(da), "l"(db), "r"(scale_d), "n"(TA), "n"(TB));
}

template<int TB>
__device__ __forceinline__ void wgmma_rs_n112(float (&d)[56], const uint32_t (&a)[4], uint64_t db, int scale_d) {
  asm volatile("{\n.reg .pred p;\nsetp.ne.b32 p, %61, 0;\n"
    "wgmma.mma_async.sync.aligned.m64n112k16.f32.bf16.bf16 {%0, %1, %2, %3, %4, %5, %6, %7, %8, %9, %10, %11, %12, %13, %14, %15, %16, %17, %18, %19, %20, %21, %22, %23, %24, %25, %26, %27, %28, %29, %30, %31, %32, %33, %34, %35, %36, %37, %38, %39, %40, %41, %42, %43, %44, %45, %46, %47, %48, %49, %50, %51, %52, %53, %54, %55}, {%56, %57, %58, %59}, %60, p, 1, 1, %62;\n}\n"
    : "+f"(d[0]), "+f"(d[1]), "+f"(d[2]), "+f"(d[3]), "+f"(d[4]), "+f"(d[5]), "+f"(d[6]), "+f"(d[7]), "+f"(d[8]), "+f"(d[9]), "+f"(d[10]), "+f"(d[11]), "+f"(d[12]), "+f"(d[13]), "+f"(d[14]), "+f"(d[15]), "+f"(d[16]), "+f"(d[17]), "+f"(d[18]), "+f"(d[19]), "+f"(d[20]), "+f"(d[21]), "+f"(d[22]), "+f"(d[23]), "+f"(d[24]), "+f"(d[25]), "+f"(d[26]), "+f"(d[27]), "+f"(d[28]), "+f"(d[29]), "+f"(d[30]), "+f"(d[31]), "+f"(d[32]), "+f"(d[33]), "+f"(d[34]), "+f"(d[35]), "+f"(d[36]), "+f"(d[37]), "+f"(d[38]), "+f"(d[39]), "+f"(d[40]), "+f"(d[41]), "+f"(d[42]), "+f"(d[43]), "+f"(d[44]), "+f"(d[45]), "+f"(d[46]), "+f"(d[47]), "+f"(d[48]), "+f"(d[49]), "+f"(d[50]), "+f"(d[51]), "+f"(d[52]), "+f"(d[53]), "+f"(d[54]), "+f"(d[55])
    : "r"(a[0]), "r"(a[1]), "r"(a[2]), "r"(a[3]), "l"(db), "r"(scale_d), "n"(TB));
}

template<int TB>
__device__ __forceinline__ void wgmma_rs_n128(float (&d)[64], const uint32_t (&a)[4], uint64_t db, int scale_d) {
  asm volatile("{\n.reg .pred p;\nsetp.ne.b32 p, %69, 0;\n"
    "wgmma.mma_async.sync.aligned.m64n128k16.f32.bf16.bf16 {%0, %1, %2, %3, %4, %5, %6, %7, %8, %9, %10, %11, %12, %13, %14, %15, %16, %17, %18, %19, %20, %21, %22, %23, %24, %25, %26, %27, %28, %29, %30, %31, %32, %33, %34, %35, %36, %37, %38, %39, %40, %41, %42, %43, %44, %45, %46, %47, %48, %49, %50, %51, %52, %53, %54, %55, %56, %57, %58, %59, %60, %61, %62, %63}, {%64, %65, %66, %67}, %68, p, 1, 1, %70;\n}\n"
    : "+f"(d[0]), "+f"(d[1]), "+f"(d[2]), "+f"(d[3]), "+f"(d[4]), "+f"(d[5]), "+f"(d[6]), "+f"(d[7]), "+f"(d[8]), "+f"(d[9]), "+f"(d[10]), "+f"(d[11]), "+f"(d[12]), "+f"(d[13]), "+f"(d[14]), "+f"(d[15]), "+f"(d[16]), "+f"(d[17]), "+f"(d[18]), "+f"(d[19]), "+f"(d[20]), "+f"(d[21]), "+f"(d[22]), "+f"(d[23]), "+f"(d[24]), "+f"(d[25]), "+f"(d[26]), "+f"(d[27]), "+f"(d[28]), "+f"(d[29]), "+f"(d[30]), "+f"(d[31]), "+f"(d[32]), "+f"(d[33]), "+f"(d[34]), "+f"(d[35]), "+f"(d[36]), "+f"(d[37]), "+f"(d[38]), "+f"(d[39]), "+f"(d[40]), "+f"(d[41]), "+f"(d[42]), "+f"(d[43]), "+f"(d[44]), "+f"(d[45]), "+f"(d[46]), "+f"(d[47]), "+f"(d[48]), "+f"(d[49]), "+f"(d[50]), "+f"(d[51]), "+f"(d[52]), "+f"(d[53]), "+f"(d[54]), "+f"(d[55]), "+f"(d[56]), "+f"(d[57]), "+f"(d[58]), "+f"(d[59]), "+f"(d[60]), "+f"(d[61]), "+f"(d[62]), "+f"(d[63])
    : "r"(a[0]), "r"(a[1]), "r"(a[2]), "r"(a[3]), "l"(db), "r"(scale_d), "n"(TB));
}

template<int TB>
__device__ __forceinline__ void wgmma_rs_n144(float (&d)[72], const uint32_t (&a)[4], uint64_t db, int scale_d) {
  asm volatile("{\n.reg .pred p;\nsetp.ne.b32 p, %77, 0;\n"
    "wgmma.mma_async.sync.aligned.m64n144k16.f32.bf16.bf16 {%0, %1, %2, %3, %4, %5, %6, %7, %8, %9, %10, %11, %12, %13, %14, %15, %16, %17, %18, %19, %20, %21, %22, %23, %24, %25, %26, %27, %28, %29, %30, %31, %32, %33, %34, %35, %36, %37, %38, %39, %40, %41, %42, %43, %44, %45, %46, %47, %48, %49, %50, %51, %52, %53, %54, %55, %56, %57, %58, %59, %60, %61, %62, %63, %64, %65, %66, %67, %68, %69, %70, %71}, {%72, %73, %74, %75}, %76, p, 1, 1, %78;\n}\n"
    : "+f"(d[0]), "+f"(d[1]), "+f"(d[2]), "+f"(d[3]), "+f"(d[4]), "+f"(d[5]), "+f"(d[6]), "+f"(d[7]), "+f"(d[8]), "+f"(d[9]), "+f"(d[10]), "+f"(d[11]), "+f"(d[12]), "+f"(d[13]), "+f"(d[14]), "+f"(d[15]), "+f"(d[16]), "+f"(d[17]), "+f"(d[18]), "+f"(d[19]), "+f"(d[20]), "+f"(d[21]), "+f"(d[22]), "+f"(d[23]), "+f"(d[24]), "+f"(d[25]), "+f"(d[26]), "+f"(d[27]), "+f"(d[28]), "+f"(d[29]), "+f"(d[30]), "+f"(d[31]), "+f"(d[32]), "+f"(d[33]), "+f"(d[34]), "+f"(d[35]), "+f"(d[36]), "+f"(d[37]), "+f"(d[38]), "+f"(d[39]), "+f"(d[40]), "+f"(d[41]), "+f"(d[42]), "+f"(d[43]), "+f"(d[44]), "+f"(d[45]), "+f"(d[46]), "+f"(d[47]), "+f"(d[48]), "+f"(d[49]), "+f"(d[50]), "+f"(d[51]), "+f"(d[52]), "+f"(d[53]), "+f"(d[54]), "+f"(d[55]), "+f"(d[56]), "+f"(d[57]), "+f"(d[58]), "+f"(d[59]), "+f"(d[60]), "+f"(d[61]), "+f"(d[62]), "+f"(d[63]), "+f"(d[64]), "+f"(d[65]), "+f"(d[66]), "+f"(d[67]), "+f"(d[68]), "+f"(d[69]), "+f"(d[70]), "+f"(d[71])
    : "r"(a[0]), "r"(a[1]), "r"(a[2]), "r"(a[3]), "l"(db), "r"(scale_d), "n"(TB));
}

__device__ __forceinline__ uint32_t pack_bf16(float lo, float hi) {
  __nv_bfloat162 v = __floats2bfloat162_rn(lo, hi);
  return *reinterpret_cast<uint32_t*>(&v);
}
__device__ __forceinline__ float bf_lo(uint32_t u) { return __uint_as_float(u << 16); }
__device__ __forceinline__ float bf_hi(uint32_t u) { return __uint_as_float(u & 0xffff0000u); }
__device__ __forceinline__ uint32_t hadd2_bf16(uint32_t a, uint32_t b) {
  __nv_bfloat162 r = __hadd2(*reinterpret_cast<__nv_bfloat162*>(&a), *reinterpret_cast<__nv_bfloat162*>(&b));
  return *reinterpret_cast<uint32_t*>(&r);
}
__device__ __forceinline__ uint32_t hmul2_bf16(uint32_t a, uint32_t b) {
  __nv_bfloat162 r = __hmul2(*reinterpret_cast<__nv_bfloat162*>(&a), *reinterpret_cast<__nv_bfloat162*>(&b));
  return *reinterpret_cast<uint32_t*>(&r);
}

template <int NV>
__device__ __forceinline__ float ln_set(uint4 (&v)[NV]) {
  float s0 = 0.f, s1 = 0.f, q0 = 0.f, q1 = 0.f, s2 = 0.f, s3 = 0.f, q2 = 0.f, q3 = 0.f;
#pragma unroll
  for (int i = 0; i < NV; i++) {
    float a = bf_lo(v[i].x), b = bf_hi(v[i].x), c = bf_lo(v[i].y), d = bf_hi(v[i].y);
    s0 += a; s1 += b; s2 += c; s3 += d;
    q0 = fmaf(a, a, q0); q1 = fmaf(b, b, q1); q2 = fmaf(c, c, q2); q3 = fmaf(d, d, q3);
    a = bf_lo(v[i].z); b = bf_hi(v[i].z); c = bf_lo(v[i].w); d = bf_hi(v[i].w);
    s0 += a; s1 += b; s2 += c; s3 += d;
    q0 = fmaf(a, a, q0); q1 = fmaf(b, b, q1); q2 = fmaf(c, c, q2); q3 = fmaf(d, d, q3);
  }
  float s = (s0 + s1) + (s2 + s3), q = (q0 + q1) + (q2 + q3);
  if (NV == 8) { s += __shfl_xor_sync(0xffffffffu, s, 4); q += __shfl_xor_sync(0xffffffffu, q, 4); }
  s += __shfl_xor_sync(0xffffffffu, s, 8); q += __shfl_xor_sync(0xffffffffu, q, 8);
  s += __shfl_xor_sync(0xffffffffu, s, 16); q += __shfl_xor_sync(0xffffffffu, q, 16);
  float mean = s * (1.0f / 512.0f);
  float var = fmaxf(fmaf(-mean, mean, q * (1.0f / 512.0f)), 0.f);
  uint32_t mv = pack_bf16(mean, var);
  uint32_t ve = pack_bf16(bf_hi(mv) + 1e-5f, 0.f);
  float sq;
  asm("sqrt.approx.ftz.f32 %0, %1;" : "=f"(sq) : "f"(bf_lo(ve)));
  uint32_t dn = pack_bf16(sq, 0.f);
  float rinv;
  asm("rcp.approx.ftz.f32 %0, %1;" : "=f"(rinv) : "f"(bf_lo(dn)));
  uint32_t m2 = __byte_perm(mv, mv, 0x1010);
  __nv_bfloat162 mb = *reinterpret_cast<__nv_bfloat162*>(&m2);
#pragma unroll
  for (int i = 0; i < NV; i++) {
    uint32_t u[4] = {v[i].x, v[i].y, v[i].z, v[i].w};
#pragma unroll
    for (int e = 0; e < 4; e++) {
      __nv_bfloat162 d = __hsub2(*reinterpret_cast<__nv_bfloat162*>(&u[e]), mb);
      u[e] = *reinterpret_cast<uint32_t*>(&d);
    }
    v[i] = make_uint4(u[0], u[1], u[2], u[3]);
  }
  return rinv;
}
__device__ __forceinline__ void ldsm_x4(uint32_t addr, uint32_t& r0, uint32_t& r1, uint32_t& r2, uint32_t& r3) {
  asm volatile("ldmatrix.sync.aligned.m8n8.x4.shared.b16 {%0,%1,%2,%3}, [%4];" : "=r"(r0), "=r"(r1), "=r"(r2), "=r"(r3) : "r"(addr));
}
__device__ __forceinline__ void ldsm_x4_t(uint32_t addr, uint32_t& r0, uint32_t& r1, uint32_t& r2, uint32_t& r3) {
  asm volatile("ldmatrix.sync.aligned.m8n8.x4.trans.shared.b16 {%0,%1,%2,%3}, [%4];" : "=r"(r0), "=r"(r1), "=r"(r2), "=r"(r3) : "r"(addr));
}
__device__ __forceinline__ void ldsm_x2(uint32_t addr, uint32_t& r0, uint32_t& r1) {
  asm volatile("ldmatrix.sync.aligned.m8n8.x2.shared.b16 {%0,%1}, [%2];" : "=r"(r0), "=r"(r1) : "r"(addr));
}
__device__ __forceinline__ void ldsm_x2_t(uint32_t addr, uint32_t& r0, uint32_t& r1) {
  asm volatile("ldmatrix.sync.aligned.m8n8.x2.trans.shared.b16 {%0,%1}, [%2];" : "=r"(r0), "=r"(r1) : "r"(addr));
}
__device__ __forceinline__ void mma16816(float (&c)[4], uint32_t a0, uint32_t a1, uint32_t a2, uint32_t a3, uint32_t b0, uint32_t b1) {
  asm("mma.sync.aligned.m16n8k16.row.col.f32.bf16.bf16.f32 {%0,%1,%2,%3}, {%4,%5,%6,%7}, {%8,%9}, {%0,%1,%2,%3};"
               : "+f"(c[0]), "+f"(c[1]), "+f"(c[2]), "+f"(c[3]) : "r"(a0), "r"(a1), "r"(a2), "r"(a3), "r"(b0), "r"(b1));
}
__device__ __forceinline__ void mma1688(float (&c)[4], uint32_t a0, uint32_t a1, uint32_t b0) {
  asm("mma.sync.aligned.m16n8k8.row.col.f32.bf16.bf16.f32 {%0,%1,%2,%3}, {%4,%5}, {%6}, {%0,%1,%2,%3};"
               : "+f"(c[0]), "+f"(c[1]), "+f"(c[2]), "+f"(c[3]) : "r"(a0), "r"(a1), "r"(b0));
}
__device__ __forceinline__ float tanh_approx(float x) { float r; asm("tanh.approx.f32 %0, %1;" : "=f"(r) : "f"(x)); return r; }
__device__ __forceinline__ float silu_f(float g) { float h = 0.5f * g; return fmaf(h, tanh_approx(h), h); }

template <int PITCH, int NU>
__device__ __forceinline__ void attn_units(uint32_t q_s, uint32_t k_s, uint32_t v_s, int u0, int ustep, int tok0, int lane, bf16* o_out) {
  const int g = lane >> 2, c = lane & 3;
  int hd[NU], tq0[NU];
  uint32_t a[NU][4], kb[NU][6], vb[NU][6];
#pragma unroll
  for (int n = 0; n < NU; n++) {
    int u = u0 + n * ustep;
    hd[n] = u >> 3; tq0[n] = 32 * (u & 3) + ((u >> 2) & 1);
    int i = (lane & 7) + ((lane >> 3) & 1) * 8;
    ldsm_x4(q_s + (tq0[n] + 2 * i) * PITCH + hd[n] * 32 + (lane >> 4) * 16, a[n][0], a[n][1], a[n][2], a[n][3]);
    int j = (lane & 7) + (lane >> 4) * 8;
    ldsm_x4(k_s + (tq0[n] + 2 + 2 * j) * PITCH + hd[n] * 32 + ((lane >> 3) & 1) * 16, kb[n][0], kb[n][1], kb[n][2], kb[n][3]);
    int row = min(tq0[n] + 2 + 2 * (16 + (lane & 7)), 143);
    ldsm_x2(k_s + row * PITCH + hd[n] * 32 + ((lane >> 3) & 1) * 16, kb[n][4], kb[n][5]);
    ldsm_x4_t(v_s + (tq0[n] + 2 + 2 * i) * PITCH + hd[n] * 32 + (lane >> 4) * 16, vb[n][0], vb[n][1], vb[n][2], vb[n][3]);
    ldsm_x2_t(v_s + row * PITCH + hd[n] * 32 + ((lane >> 3) & 1) * 16, vb[n][4], vb[n][5]);
  }
  float sc[NU][3][4];
#pragma unroll
  for (int n = 0; n < NU; n++)
#pragma unroll
    for (int nt = 0; nt < 3; nt++) {
#pragma unroll
      for (int e = 0; e < 4; e++) sc[n][nt][e] = 0.f;
      mma16816(sc[n][nt], a[n][0], a[n][1], a[n][2], a[n][3], kb[n][2 * nt], kb[n][2 * nt + 1]);
    }
  const bool lo0 = (2 * c) >= g, lo1 = (2 * c + 1) >= g;
  float l[NU][4], m0[NU], m1[NU];
#pragma unroll
  for (int n = 0; n < NU; n++) {
    uint32_t p0 = pack_bf16(lo0 ? sc[n][0][0] : sc[n][1][0], lo1 ? sc[n][0][1] : sc[n][1][1]);
    uint32_t p1 = pack_bf16(lo0 ? sc[n][1][2] : sc[n][2][2], lo1 ? sc[n][1][3] : sc[n][2][3]);
    l[n][0] = bf_lo(p0) * 0.25f; l[n][1] = bf_hi(p0) * 0.25f; l[n][2] = bf_lo(p1) * 0.25f; l[n][3] = bf_hi(p1) * 0.25f;
    int kb0 = tok0 + tq0[n] - 14 + 4 * c;
    if (kb0 < 0) {
      if (kb0 + (lo0 ? 0 : 16) < 0) l[n][0] = -1e9f;
      if (kb0 + (lo1 ? 2 : 18) < 0) l[n][1] = -1e9f;
      if (kb0 + (lo0 ? 16 : 32) < 0) l[n][2] = -1e9f;
      if (kb0 + (lo1 ? 18 : 34) < 0) l[n][3] = -1e9f;
    }
    m0[n] = fmaxf(l[n][0], l[n][1]); m1[n] = fmaxf(l[n][2], l[n][3]);
  }
#pragma unroll
  for (int o = 1; o <= 2; o <<= 1)
#pragma unroll
    for (int n = 0; n < NU; n++) {
      m0[n] = fmaxf(m0[n], __shfl_xor_sync(0xffffffffu, m0[n], o)); m1[n] = fmaxf(m1[n], __shfl_xor_sync(0xffffffffu, m1[n], o));
    }
  float s0[NU], s1[NU];
#pragma unroll
  for (int n = 0; n < NU; n++) {
    l[n][0] = __expf(l[n][0] - m0[n]); l[n][1] = __expf(l[n][1] - m0[n]);
    l[n][2] = __expf(l[n][2] - m1[n]); l[n][3] = __expf(l[n][3] - m1[n]);
    s0[n] = l[n][0] + l[n][1]; s1[n] = l[n][2] + l[n][3];
  }
#pragma unroll
  for (int o = 1; o <= 2; o <<= 1)
#pragma unroll
    for (int n = 0; n < NU; n++) {
      s0[n] += __shfl_xor_sync(0xffffffffu, s0[n], o); s1[n] += __shfl_xor_sync(0xffffffffu, s1[n], o);
    }
  const uint32_t mlo = (lo0 ? 0x0000ffffu : 0u) | (lo1 ? 0xffff0000u : 0u);
#pragma unroll
  for (int n = 0; n < NU; n++) {
    float r0 = __fdividef(1.0f, s0[n]), r1 = __fdividef(1.0f, s1[n]);
    uint32_t q0 = pack_bf16(l[n][0] * r0, l[n][1] * r0), q1 = pack_bf16(l[n][2] * r1, l[n][3] * r1);
    uint32_t pa[3][2];
    pa[0][0] = q0 & mlo; pa[1][0] = q0 & ~mlo; pa[2][0] = 0u;
    pa[0][1] = 0u; pa[1][1] = q1 & mlo; pa[2][1] = q1 & ~mlo;
    float o0[4] = {0.f, 0.f, 0.f, 0.f}, o1[4] = {0.f, 0.f, 0.f, 0.f};
    mma16816(o0, pa[0][0], pa[0][1], pa[1][0], pa[1][1], vb[n][0], vb[n][1]);
    mma16816(o1, pa[0][0], pa[0][1], pa[1][0], pa[1][1], vb[n][2], vb[n][3]);
    mma1688(o0, pa[2][0], pa[2][1], vb[n][4]);
    mma1688(o1, pa[2][0], pa[2][1], vb[n][5]);
    bf16* p0 = o_out + ((size_t)(hd[n] * 2) * 128 + tq0[n] + 2 * g) * 8 + 2 * c;
    *reinterpret_cast<uint32_t*>(p0) = pack_bf16(o0[0], o0[1]);
    *reinterpret_cast<uint32_t*>(p0 + 128 * 8) = pack_bf16(o1[0], o1[1]);
    *reinterpret_cast<uint32_t*>(p0 + 16 * 8) = pack_bf16(o0[2], o0[3]);
    *reinterpret_cast<uint32_t*>(p0 + 128 * 8 + 16 * 8) = pack_bf16(o1[2], o1[3]);
  }
}

__device__ float2 g_stats[16 * 8 * 128];
__device__ unsigned g_cnt_o[16 * 32], g_cnt_h[16 * 32], g_flag_act[16 * 16 * 32];
__device__ unsigned g_epoch, g_done;

constexpr int K1_XCH = 152 * 128;
constexpr int K1_ACT_BYTES = 8 * K1_XCH;
constexpr int K1_STAGE = 3 * 8192;
constexpr int K1_NST = 3;
constexpr int K1_PITCH = 144;
constexpr int K3_STAGE = 4 * 8192;
constexpr int K3_NST = 3;
constexpr int K4_STAGE = 57344;
constexpr int K4_NST = 3;
constexpr int OFF_WST1 = K1_ACT_BYTES;
constexpr int OFF_B2 = 0, OFF_A2 = 65536;
constexpr int OFF_A3 = 0, OFF_WST3 = 131072;
constexpr int OFF_ST4 = 0, OFF_RED = K4_NST * K4_STAGE;
constexpr int OFF_BARS = 229376, OFF_RINV = OFF_BARS + 512, OFF_CSV = OFF_RINV + 1152, OFF_MISC = OFF_CSV + 256;
constexpr int MK_SMEM = OFF_MISC + 64 + 1024;
constexpr int B_FULL1 = 0, B_EMPTY1 = 3, B_P1MAIN = 6, B_P1ATT = 7, B_FULL2 = 8, B_P2MAIN = 16, B_FULL3 = 17, B_EMPTY3 = 20, B_AFULL3 = 23,
              B_P3MAIN = 31, B_FULL4 = 32, B_EMPTY4 = 35, B_X4 = 38, B_RDY4 = 39, B_H3 = 40, B_H4 = 41, B_HST = 42, B_OST = 43, B_HDONE = 44, B_ACT0 = 45, B_ACT1 = 46, B_XF = 47, B_STATS = 55, B_A3F = 56;
constexpr int OFF_OST = 65536, OFF_AST = 200704;

__device__ __forceinline__ unsigned ld_acquire(const unsigned* p) {
  unsigned v;
  asm volatile("ld.relaxed.gpu.global.u32 %0, [%1];" : "=r"(v) : "l"(p) : "memory");
  return v;
}
__device__ __forceinline__ void wait_flag(const unsigned* p, unsigned target) {
  for (uint32_t it = 0; (int)(ld_acquire(p) - target) < 0; it++) {
    __nanosleep(40);
    if (it > (1u << 22)) __trap();
  }
}
__device__ __forceinline__ void signal_flag(unsigned* p) {
  asm volatile("red.release.gpu.global.add.u32 [%0], 1;" ::"l"(p) : "memory");
}
__device__ __forceinline__ void signal_flag_relaxed(unsigned* p) {
  asm volatile("red.relaxed.gpu.global.add.u32 [%0], 1;" ::"l"(p) : "memory");
}
__device__ __forceinline__ void bulk_store(void* dst, uint32_t src, uint32_t bytes) {
  asm volatile("cp.async.bulk.global.shared::cta.bulk_group [%0], [%1], %2;" ::"l"(dst), "r"(src), "r"(bytes) : "memory");
}
__device__ __forceinline__ void bulk_commit_wait() {
  asm volatile("cp.async.bulk.commit_group;" ::: "memory");
  asm volatile("cp.async.bulk.wait_group 0;" ::: "memory");
}
__device__ __forceinline__ void fence_proxy_async_all() { asm volatile("fence.proxy.async;" ::: "memory"); }
__device__ __forceinline__ void ln_finish(float s, float q, uint32_t& mean2, float& rinv) {
  float mean = s * (1.0f / 512.0f);
  float var = fmaxf(fmaf(-mean, mean, q * (1.0f / 512.0f)), 0.f);
  uint32_t mv = pack_bf16(mean, var);
  uint32_t ve = pack_bf16(bf_hi(mv) + 1e-5f, 0.f);
  float sq;
  asm("sqrt.approx.ftz.f32 %0, %1;" : "=f"(sq) : "f"(bf_lo(ve)));
  uint32_t dn = pack_bf16(sq, 0.f);
  asm("rcp.approx.ftz.f32 %0, %1;" : "=f"(rinv) : "f"(bf_lo(dn)));
  mean2 = __byte_perm(mv, mv, 0x1010);
}
__device__ __forceinline__ uint32_t hsub2_bf16(uint32_t a, uint32_t b) {
  __nv_bfloat162 r = __hsub2(*reinterpret_cast<__nv_bfloat162*>(&a), *reinterpret_cast<__nv_bfloat162*>(&b));
  return *reinterpret_cast<uint32_t*>(&r);
}

__device__ __forceinline__ void p4_issue_w(const CUtensorMap* tm_wd, uint32_t sbase, uint32_t bars, int it, int nb, int cr) {
  int s = it % K4_NST, hs = cr * 4 + (it & 3), p = it >> 2;
  mbar_expect_tx(bars + 8 * (B_FULL4 + s), K4_STAGE);
  uint32_t d = sbase + OFF_ST4 + s * K4_STAGE;
  int k0 = hs * 224 + p * 112;
  tma_2d(d + 28672, tm_wd, nb * 128, k0, bars + 8 * (B_FULL4 + s));
  tma_2d(d + 28672 + 14336, tm_wd, nb * 128 + 64, k0, bars + 8 * (B_FULL4 + s));
}
__device__ __forceinline__ void p4_issue_a(uint32_t sbase, uint32_t bars, int it, int rb, int cr) {
  int s = it % K4_NST, hs = cr * 4 + (it & 3), p = it >> 2;
  bulk_load(sbase + OFF_ST4 + s * K4_STAGE, g_act + (size_t)(rb * 224 + hs * 28 + p * 14) * 1024, 28672, bars + 8 * (B_FULL4 + s));
}
__device__ __forceinline__ void wait_flags4(const unsigned* f, unsigned ep1) {
  for (uint32_t n = 0;; n++) {
    unsigned f0 = ld_acquire(f), f1 = ld_acquire(f + 64), f2 = ld_acquire(f + 128), f3 = ld_acquire(f + 192);
    if ((int)(f0 - ep1) >= 0 && (int)(f1 - ep1) >= 0 && (int)(f2 - ep1) >= 0 && (int)(f3 - ep1) >= 0) break;
    __nanosleep(40);
    if (n > (1u << 22)) __trap();
  }
  fence_proxy_async_all();
}
__device__ __forceinline__ void p1_issue(const CUtensorMap* tm, uint32_t wst, uint32_t bars, int kc, int hg, int cr) {
  int s = kc % K1_NST;
  mbar_expect_tx(bars + 8 * (B_FULL1 + s), K1_STAGE);
#pragma unroll
  for (int w = 0; w < 3; w++)
    tma_2d_mc(wst + s * K1_STAGE + w * 8192 + cr * 4096, tm, w * 512 + hg * 64, kc * 64 + cr * 32, bars + 8 * (B_FULL1 + s), 3);
}
template <int NT, int NA>
__device__ __forceinline__ void p1_stage(const float (&acc)[NA], float cs0, float cs1, uint32_t stg, const float2* mr, int lane, int w4) {
  int c = lane & 3;
#pragma unroll
  for (int j = 0; j < NT / 8; j += 2) {
    uint32_t r[4];
#pragma unroll
    for (int jj = 0; jj < 2; jj++) {
      if (j + jj < NT / 8) {
        float4 m = *reinterpret_cast<const float4*>(mr + 8 * (j + jj) + 2 * c);
        r[2 * jj] = pack_bf16(fmaf(-m.x, cs0, acc[4 * (j + jj) + 0]) * m.y, fmaf(-m.z, cs0, acc[4 * (j + jj) + 1]) * m.w);
        r[2 * jj + 1] = pack_bf16(fmaf(-m.x, cs1, acc[4 * (j + jj) + 2]) * m.y, fmaf(-m.z, cs1, acc[4 * (j + jj) + 3]) * m.w);
      }
    }
    int tok = 8 * (j + (lane >> 4)) + (lane & 7);
    uint32_t addr = stg + tok * K1_PITCH + (16 * w4 + 8 * ((lane >> 3) & 1)) * 2;
    if (j + 1 < NT / 8)
      asm volatile("stmatrix.sync.aligned.m8n8.x4.trans.shared.b16 [%0], {%1,%2,%3,%4};" ::"r"(addr), "r"(r[0]), "r"(r[1]), "r"(r[2]), "r"(r[3]) : "memory");
    else {
      addr = stg + (8 * j + (lane & 7)) * K1_PITCH + (16 * w4 + 8 * ((lane >> 3) & 1)) * 2;
      asm volatile("stmatrix.sync.aligned.m8n8.x2.trans.shared.b16 [%0], {%1,%2};" ::"r"(addr), "r"(r[0]), "r"(r[1]) : "memory");
    }
  }
}
template <int WG, int N, int NV, typename F, typename FV>
__device__ __forceinline__ void p1_mainloop_store(F mma, FV mmav, uint32_t sbase, uint8_t* sptr, uint32_t bars, uint32_t bars_peer, int tid_wg) {
  const uint32_t full0 = bars + 8 * B_FULL1, empty0 = bars + 8 * B_EMPTY1, empty0_peer = bars_peer + 8 * B_EMPTY1;
  const uint32_t wst = sbase + OFF_WST1, act = sbase + (WG == 0 ? 16 * 128 : 0), actv = sbase + (WG == 0 ? 0 : 72 * 128);
  float acc[N / 2], accv[NV / 2];
#pragma unroll 1
  for (int kc = 0; kc < 8; kc++) {
    const int s = kc % K1_NST, sp = (kc + K1_NST - 1) % K1_NST;
    bool rel = (kc == 0) || (kc - 1 >= 8 - K1_NST);
    mbar_wait(bars + 8 * (B_XF + kc), 0);
    if (!mbar_try(full0 + 8 * s, (kc / K1_NST) & 1)) {
      if (!rel) {
        wgmma_wait<0>();
        if (tid_wg == 0) { mbar_arrive(empty0 + 8 * sp); mbar_arrive_cluster(empty0_peer + 8 * sp); }
        rel = true;
      }
      mbar_wait(full0 + 8 * s, (kc / K1_NST) & 1);
    }
    if (kc == 0 && WG == 0 && tid_wg == 0) DBG(1, 1);
    wgmma_fence();
#pragma unroll
    for (int ks = 0; ks < 4; ks++) {
      uint64_t da = make_desc(wst + s * K1_STAGE + WG * 8192 + ks * 2048, 8192, 1024);
      uint64_t dv = make_desc(wst + s * K1_STAGE + 16384 + ks * 2048, 8192, 1024);
      uint64_t db = make_desc(act + kc * K1_XCH + ks * 32, 16, 1024);
      uint64_t dbv = make_desc(actv + kc * K1_XCH + ks * 32, 16, 1024);
      mma(acc, da, db, (kc | ks) != 0);
      mmav(accv, dv, dbv, (kc | ks) != 0);
    }
    wgmma_commit();
    wgmma_wait<1>();
    if (!rel && tid_wg == 0) { mbar_arrive(empty0 + 8 * sp); mbar_arrive_cluster(empty0_peer + 8 * sp); }
  }
  wgmma_wait<0>();
  int lane = tid_wg & 31, w4 = tid_wg >> 5, g = lane >> 2;
  float* s_csv = reinterpret_cast<float*>(sptr + OFF_CSV);
  if (WG == 1 && (lane & 3) == 0) { s_csv[16 * w4 + g] = accv[36]; s_csv[16 * w4 + g + 8] = accv[38]; }
  mbar_wait(bars + 8 * B_STATS, 0);
  if (tid_wg == 0) mbar_arrive(bars + 8 * B_P1MAIN);
  named_bar_sync(2, 256);
  const float2* mr = reinterpret_cast<const float2*>(sptr + OFF_RINV);
  uint32_t stq = wst, stk = wst + 128 * K1_PITCH, stv = stk + 144 * K1_PITCH;
  float cs0 = __shfl_sync(0xffffffffu, acc[N / 2 - 4], lane & ~3), cs1 = __shfl_sync(0xffffffffu, acc[N / 2 - 2], lane & ~3);
  float cv0 = s_csv[16 * w4 + g], cv1 = s_csv[16 * w4 + g + 8];
  if (WG == 0) {
    p1_stage<128>(acc, cs0, cs1, stq, mr + 16, lane, w4);
    p1_stage<72>(accv, cv0, cv1, stv, mr, lane, w4);
  } else {
    p1_stage<144>(acc, cs0, cs1, stk, mr, lane, w4);
    p1_stage<72>(accv, cv0, cv1, stv + 72 * K1_PITCH, mr + 72, lane, w4);
  }
}
__device__ __forceinline__ void p1_stats(uint8_t* sptr, uint32_t bars, int w3, int lane) {
  float2* mr = reinterpret_cast<float2*>(sptr + OFF_RINV);
  int gq = lane >> 2, rr = lane & 3;
  float s[12], q[12];
#pragma unroll
  for (int st = 0; st < 12; st++) { s[st] = 0.f; q[st] = 0.f; }
  const uint8_t* base = sptr + (w3 * 48 + rr) * 128;
#pragma unroll 1
  for (int kc = 0; kc < 8; kc++) {
    mbar_wait(bars + 8 * (B_XF + kc), 0);
#pragma unroll
    for (int st = 0; st < 12; st++) {
      uint4 t = *reinterpret_cast<const uint4*>(base + kc * K1_XCH + st * 512 + ((gq ^ ((st * 4 + rr) & 7)) << 4));
      uint32_t u[4] = {t.x, t.y, t.z, t.w};
#pragma unroll
      for (int e = 0; e < 4; e++) {
        float lo = bf_lo(u[e]), hi = bf_hi(u[e]);
        s[st] += lo + hi; q[st] = fmaf(lo, lo, fmaf(hi, hi, q[st]));
      }
    }
  }
#pragma unroll
  for (int st = 0; st < 12; st++) {
#pragma unroll
    for (int o = 4; o <= 16; o <<= 1) { s[st] += __shfl_xor_sync(0xffffffffu, s[st], o); q[st] += __shfl_xor_sync(0xffffffffu, q[st], o); }
    uint32_t m2; float ri;
    ln_finish(s[st], q[st], m2, ri);
    if (gq == 0) mr[w3 * 48 + st * 4 + rr] = make_float2(bf_lo(m2), ri);
  }
  __syncwarp();
  if (lane == 0) mbar_arrive(bars + 8 * B_STATS);
}
__device__ __forceinline__ void p1_attn(uint32_t sbase, uint8_t* sptr, uint32_t bars, int rb, int tid) {
  int warp = tid >> 5, lane = tid & 31;
  uint32_t stq = sbase + OFF_WST1, stk = stq + 128 * K1_PITCH, stv = stk + 144 * K1_PITCH;
  named_bar_sync(1, 384);
  if (tid == 0) DBG(1, 2);
  {
    bf16* op = reinterpret_cast<bf16*>(sptr + OFF_OST);
    if (warp < 8) attn_units<K1_PITCH, 3>(stq, stk, stv, warp, 12, rb * 128, lane, op);
    else attn_units<K1_PITCH, 2>(stq, stk, stv, warp, 12, rb * 128, lane, op);
  }
  fence_proxy_async();
  mbar_arrive(bars + 8 * B_OST);
  if (tid == 0) DBG(1, 4);
}

__global__ void __launch_bounds__(384, 1)
    mega(const __grid_constant__ CUtensorMap tm_wqkv, const __grid_constant__ CUtensorMap tm_wo, const __grid_constant__ CUtensorMap tm_wg,
         const __grid_constant__ CUtensorMap tm_wu, const __grid_constant__ CUtensorMap tm_wd, const __grid_constant__ CUtensorMap tm_out,
         const __grid_constant__ CUtensorMap tm_x, const bf16* __restrict__ x, const bf16* __restrict__ wqkv, const bf16* __restrict__ wo,
         const bf16* __restrict__ wg_, const bf16* __restrict__ wu_, const bf16* __restrict__ wd_) {
  extern __shared__ uint8_t smem_raw[];
  uint32_t sbase = (smem_u32(smem_raw) + 1023) & ~1023u;
  uint8_t* sptr = smem_raw + (sbase - smem_u32(smem_raw));
  const uint32_t bars = sbase + OFF_BARS;
  const int b = blockIdx.x, cr = b & 1;
  const int rbA = (b >> 4) * 2 + cr, slA = (b >> 1) & 7;
  const int rbB = b >> 3;
  int tid = threadIdx.x, warp = tid >> 5, lane = tid & 31;
  if (tid == 0) DBG(1, 0);
  if (tid < 256) {
#pragma unroll
    for (int i = 0; i < 2; i++) {
      int idx = tid + i * 256, kc = idx >> 6, w = idx & 63;
      uint32_t val = (w < 8) ? 0x3F803F80u : 0u;
      *reinterpret_cast<uint4*>(sptr + kc * K1_XCH + 144 * 128 + w * 16) = make_uint4(val, val, val, val);
    }
    fence_proxy_async();
  }
  if (tid == 256) {
    for (int i = 0; i < 8; i++) mbar_init(bars + 8 * (B_XF + i), 1);
    fence_barrier_init();
    for (int kc = 0; kc < 2; kc++) {
      mbar_expect_tx(bars + 8 * (B_XF + kc), 144 * 128);
      tma_2d(sbase + kc * K1_XCH, &tm_x, kc * 64, rbA * 128 - 16, bars + 8 * (B_XF + kc));
    }
  }
  if (tid == 288) {
    asm volatile("prefetch.tensormap [%0];" ::"l"(&tm_wqkv) : "memory");
    for (int i = 0; i < 3; i++) { mbar_init(bars + 8 * (B_FULL1 + i), 1); mbar_init(bars + 8 * (B_EMPTY1 + i), 4); }
    mbar_init(bars + 8 * B_P1MAIN, 2);
    mbar_init(bars + 8 * B_P1ATT, 2);
    for (int i = 0; i < 8; i++) { mbar_init(bars + 8 * (B_FULL2 + i), 1); mbar_init(bars + 8 * (B_AFULL3 + i), 1); }
    mbar_init(bars + 8 * B_P2MAIN, 4);
    for (int i = 0; i < 3; i++) { mbar_init(bars + 8 * (B_FULL3 + i), 1); mbar_init(bars + 8 * (B_EMPTY3 + i), 4); }
    mbar_init(bars + 8 * B_P3MAIN, 2);
    for (int i = 0; i < 3; i++) { mbar_init(bars + 8 * (B_FULL4 + i), 1); mbar_init(bars + 8 * (B_EMPTY4 + i), 2); }
    mbar_init(bars + 8 * B_X4, 1);
    mbar_init(bars + 8 * B_RDY4, 1);
    mbar_init(bars + 8 * B_H3, 1);
    mbar_init(bars + 8 * B_H4, 1);
    mbar_init(bars + 8 * B_HST, 256);
    mbar_init(bars + 8 * B_OST, 384);
    mbar_init(bars + 8 * B_HDONE, 1);
    mbar_init(bars + 8 * B_ACT0, 256);
    mbar_init(bars + 8 * B_ACT1, 256);
    mbar_init(bars + 8 * B_STATS, 3);
    mbar_init(bars + 8 * B_A3F, 8);
    mbar_init(bars + 8 * (B_A3F + 1), 8);
    fence_barrier_init();
    mbar_expect_tx(bars + 8 * B_X4, 32768);
  }
  if (tid == 256) DBG(1, 5);
  __syncthreads();
  cluster_arrive_relaxed();
  const uint32_t bars_peer = mapa(bars, cr ^ 1);

  if (warp >= 8) {
    if (tid == 256) DBG(1, 6);
    cluster_wait();
    if (tid == 256) DBG(1, 7);
    if (warp > 8) {
      p1_stats(sptr, bars, warp - 9, lane);
      int t = tid - 288;
      if (t < 32) asm volatile("prefetch.global.L2 [%0];" ::"l"(wo + (size_t)(b * 32 + t) * 64));
      for (int i = t; i < 112; i += 96) {
        asm volatile("prefetch.global.L2 [%0];" ::"l"(wg_ + (size_t)(b * 112 + i) * 64));
        asm volatile("prefetch.global.L2 [%0];" ::"l"(wu_ + (size_t)(b * 112 + i) * 64));
        asm volatile("prefetch.global.L2 [%0];" ::"l"(wd_ + (size_t)(b * 112 + i) * 64));
      }
    }
    unsigned ep1 = 0;
    if (tid == 256) {
      for (int kc = 0; kc < 8; kc++) {
        if (kc >= K1_NST)
        mbar_wait(bars + 8 * (B_EMPTY1 + kc % K1_NST), ((kc / K1_NST) - 1) & 1);
        p1_issue(&tm_wqkv, sbase + OFF_WST1, bars, kc, slA, cr);
        if (kc < 3) {
          for (int k = 2 + 2 * kc; k < 4 + 2 * kc; k++) {
            mbar_expect_tx(bars + 8 * (B_XF + k), 144 * 128);
            tma_2d(sbase + k * K1_XCH, &tm_x, k * 64, rbA * 128 - 16, bars + 8 * (B_XF + k));
          }
        }
      }
      ep1 = *reinterpret_cast<volatile unsigned*>(&g_epoch) + 1;
      mbar_wait(bars + 8 * B_P1MAIN, 0);
      for (int kc = 0; kc < 8; kc++) {
        mbar_expect_tx(bars + 8 * (B_FULL2 + kc), 16384 + 8192);
        tma_2d(sbase + OFF_B2 + kc * 8192, &tm_wo, (b & 7) * 64, kc * 64, bars + 8 * (B_FULL2 + kc));
      }
    }
    __syncwarp();
    p1_attn(sbase, sptr, bars, rbA, tid);
    if (tid == 256) {
      mbar_wait(bars + 8 * B_P1ATT, 0);
      wait_flag(&g_cnt_o[rbB * 32], 8 * ep1);
      fence_proxy_async_all();
      DBG(2, 1);
      for (int kc = 0; kc < 8; kc++)
        bulk_load_mc(sbase + OFF_A2 + kc * 16384 + cr * 8192, g_o + (size_t)(rbB * 64 + kc * 8 + cr * 4) * 1024, 8192, bars + 8 * (B_FULL2 + kc), 3);
      mbar_wait(bars + 8 * B_P2MAIN, 0);
      {
        const CUtensorMap* tm = cr ? &tm_wu : &tm_wg;
        for (int it = 0; it < 16; it++) {
          int s = it % K3_NST, p = it >> 3, kc = it & 7;
          if (it == K3_NST) {
            mbar_wait(bars + 8 * B_HDONE, 0);
            wait_flag(&g_cnt_h[rbA * 32], 8 * ep1);
            mbar_arrive(bars + 8 * B_H3);
            fence_proxy_async_all();
            DBG(3, 1);
            for (int k = 0; k < 8; k++) {
              mbar_expect_tx(bars + 8 * (B_AFULL3 + k), 16384);
              bulk_load(sbase + OFF_A3 + k * 16384, g_h + (size_t)(rbA * 64 + k * 8) * 1024, 16384, bars + 8 * (B_AFULL3 + k));
            }
          }
          if (it >= K3_NST) mbar_wait(bars + 8 * (B_EMPTY3 + s), ((it / K3_NST) - 1) & 1);
          mbar_expect_tx(bars + 8 * (B_FULL3 + s), K3_STAGE);
          uint32_t d = sbase + OFF_WST3 + s * K3_STAGE + cr * 16384;
          tma_3d_mc(d, tm, 0, slA * 2 + p, kc * 64, bars + 8 * (B_FULL3 + s), 3);
          tma_3d_mc(d + 8192, tm, 64, slA * 2 + p, kc * 64, bars + 8 * (B_FULL3 + s), 3);
        }
      }
      mbar_wait(bars + 8 * B_P3MAIN, 0);
      mbar_wait(bars + 8 * B_H4, 0);
      fence_proxy_async_all();
      bool all1 = false;
      for (int it = 2; it < 8; it++) {
        if (it >= K4_NST) mbar_wait(bars + 8 * (B_EMPTY4 + it % K4_NST), ((it / K4_NST) - 1) & 1);
        p4_issue_w(&tm_wd, sbase, bars, it, (b >> 1) & 3, cr);
        if (it >= 4 && !all1) {
          const unsigned* f = &g_flag_act[(rbB * 16 + cr * 8 + 1) * 32];
          unsigned f0 = ld_acquire(f), f1 = ld_acquire(f + 64), f2 = ld_acquire(f + 128), f3 = ld_acquire(f + 192);
          all1 = (int)(f0 - ep1) >= 0 && (int)(f1 - ep1) >= 0 && (int)(f2 - ep1) >= 0 && (int)(f3 - ep1) >= 0;
          if (!all1) wait_flag(f + (it - 4) * 64, ep1);
          fence_proxy_async_all();
        }
        p4_issue_a(sbase, bars, it, rbB, cr);
      }
    }
    if (tid == 288) {
      mbar_wait(bars + 8 * B_OST, 0);
      bulk_store(g_o + (size_t)(rbA * 64 + slA * 8) * 1024, sbase + OFF_OST, 16384);
      bulk_commit_wait();
      signal_flag_relaxed(&g_cnt_o[rbA * 32]);
      mbar_arrive(bars + 8 * B_P1ATT);
      mbar_arrive_cluster(bars_peer + 8 * B_P1ATT);
      DBG(1, 3);
      mbar_wait(bars + 8 * B_HST, 0);
      bulk_store(g_h + (size_t)(rbB * 64 + (b & 7) * 8) * 1024, sbase, 16384);
      bulk_store(&g_stats[(rbB * 8 + (b & 7)) * 128], sbase + 16384, 1024);
      bulk_commit_wait();
      signal_flag_relaxed(&g_cnt_h[rbB * 32]);
      mbar_arrive(bars + 8 * B_HDONE);
      DBG(2, 3);
      mbar_wait(bars + 8 * B_ACT0, 0);
      signal_flag(&g_flag_act[(rbA * 16 + slA * 2) * 32]);
      DBG(3, 7);
      ep1 = *reinterpret_cast<volatile unsigned*>(&g_epoch) + 1;
      wait_flag(&g_cnt_h[rbB * 32], 8 * ep1);
      wait_flags4(&g_flag_act[(rbB * 16 + cr * 8) * 32], ep1);
      mbar_arrive(bars + 8 * B_H4);
      for (int it = 0; it < 2; it++) {
        mbar_wait(bars + 8 * (B_A3F + it), 0);
        if (it == 0) DBG(4, 1);
        p4_issue_w(&tm_wd, sbase, bars, it, (b >> 1) & 3, cr);
        p4_issue_a(sbase, bars, it, rbB, cr);
      }
      mbar_wait(bars + 8 * B_ACT1, 0);
      bulk_store(g_act + (size_t)(rbA * 224 + slA * 28 + 14) * 1024, sbase + OFF_AST, 28672);
      bulk_commit_wait();
      signal_flag_relaxed(&g_flag_act[(rbA * 16 + slA * 2 + 1) * 32]);
      mbar_arrive_cluster(bars_peer + 8 * B_RDY4);
      DBG(3, 8);
    }
    __syncwarp();
    cluster_arrive_relaxed();
    cluster_wait();
  } else {
    const int wg = warp >> 2, w4 = warp & 3, tid_wg = tid & 127;
    cluster_wait();
    if (wg == 0)
      p1_mainloop_store<0, 136, 72>([](float (&d)[68], uint64_t a, uint64_t bb, int s) { wgmma_n136<1, 0>(d, a, bb, s); },
                                    [](float (&d)[36], uint64_t a, uint64_t bb, int s) { wgmma_n72<1, 0>(d, a, bb, s); }, sbase, sptr, bars, bars_peer, tid_wg);
    else
      p1_mainloop_store<1, 152, 80>([](float (&d)[76], uint64_t a, uint64_t bb, int s) { wgmma_n152<1, 0>(d, a, bb, s); },
                                    [](float (&d)[40], uint64_t a, uint64_t bb, int s) { wgmma_n80<1, 0>(d, a, bb, s); }, sbase, sptr, bars, bars_peer, tid_wg);
    p1_attn(sbase, sptr, bars, rbA, tid);
    const int g = lane >> 2, c = lane & 3;
    const int rl = wg * 64 + w4 * 16 + g;
    {
      const int rb = rbB, nb = b & 7;
      uint32_t xr[16];
#pragma unroll
      for (int j = 0; j < 8; j++)
#pragma unroll
        for (int hh = 0; hh < 2; hh++)
          xr[2 * j + hh] = __ldg(reinterpret_cast<const uint32_t*>(x + (size_t)(rb * 128 + rl + 8 * hh) * D_ + nb * 64 + 8 * j + 2 * c));
      float acc[32];
#pragma unroll 1
      for (int kc = 0; kc < 8; kc++) {
        mbar_wait(bars + 8 * (B_FULL2 + kc), 0);
        wgmma_fence();
#pragma unroll
        for (int ks = 0; ks < 4; ks++) {
          uint64_t da = make_desc_ns(sbase + OFF_A2 + kc * 16384 + ks * 4096 + wg * 1024, 2048, 128);
          uint64_t db = make_desc(sbase + OFF_B2 + kc * 8192 + ks * 2048, 8192, 1024);
          wgmma_n64<0, 1>(acc, da, db, (kc | ks) != 0);
        }
        wgmma_commit();
      }
      wgmma_wait<0>();
      if (tid_wg == 0) { mbar_arrive(bars + 8 * B_P2MAIN); mbar_arrive_cluster(bars_peer + 8 * B_P2MAIN); }
      if (tid == 0) DBG(2, 2);
      named_bar_sync(2, 256);
      float ss[2] = {0.f, 0.f}, qq[2] = {0.f, 0.f};
#pragma unroll
      for (int j = 0; j < 8; j++)
#pragma unroll
        for (int hh = 0; hh < 2; hh++) {
          uint32_t hv = hadd2_bf16(xr[2 * j + hh], pack_bf16(acc[4 * j + 2 * hh], acc[4 * j + 2 * hh + 1]));
          *reinterpret_cast<uint32_t*>(sptr + j * 2048 + (rl + 8 * hh) * 16 + 4 * c) = hv;
          float lo = bf_lo(hv), hi = bf_hi(hv);
          ss[hh] += lo + hi;
          qq[hh] = fmaf(lo, lo, fmaf(hi, hi, qq[hh]));
        }
#pragma unroll
      for (int hh = 0; hh < 2; hh++) {
        ss[hh] += __shfl_xor_sync(0xffffffffu, ss[hh], 1); qq[hh] += __shfl_xor_sync(0xffffffffu, qq[hh], 1);
        ss[hh] += __shfl_xor_sync(0xffffffffu, ss[hh], 2); qq[hh] += __shfl_xor_sync(0xffffffffu, qq[hh], 2);
        if (c == 0) *reinterpret_cast<float2*>(sptr + 16384 + (rl + 8 * hh) * 8) = make_float2(ss[hh], qq[hh]);
      }
      fence_proxy_async();
      mbar_arrive(bars + 8 * B_HST);
      if (tid == 0) DBG(2, 4);
    }
    {
      const int rb = rbA, hs = slA;
      const uint32_t full0 = bars + 8 * B_FULL3, empty0 = bars + 8 * B_EMPTY3, empty0_peer = bars_peer + 8 * B_EMPTY3, afull0 = bars + 8 * B_AFULL3;
      const uint32_t wst = sbase + OFF_WST3;
      mbar_wait(bars + 8 * B_H3, 0);
      uint32_t m2[2];
      float ri[2];
#pragma unroll
      for (int hh = 0; hh < 2; hh++) {
        float s = 0.f, q = 0.f;
#pragma unroll
        for (int n = 0; n < 8; n++) { float2 t = __ldcg(&g_stats[(rb * 8 + n) * 128 + rl + 8 * hh]); s += t.x; q += t.y; }
        ln_finish(s, q, m2[hh], ri[hh]);
      }
      if (tid == 0) DBG(3, 2);
      uint32_t a_off = sbase + OFF_A3 + (lane >> 4) * 2048 + (wg * 64 + w4 * 16 + (lane & 15)) * 16;
#pragma unroll 1
      for (int p = 0; p < 2; p++) {
        float ag[56], au[56];
        uint32_t af[4][4];
#pragma unroll 1
        for (int kc = 0; kc < 8; kc++) {
          int it = p * 8 + kc, s = it % K3_NST, sp = (it + K3_NST - 1) % K3_NST;
          bool rel = (kc == 0) || (it - 1 >= 16 - K3_NST);
          if (p == 0) mbar_wait(afull0 + 8 * kc, 0);
          if (!mbar_try(full0 + 8 * s, (it / K3_NST) & 1)) {
            if (!rel) {
              wgmma_wait<0>();
              if (tid_wg == 0) { mbar_arrive(empty0 + 8 * sp); mbar_arrive_cluster(empty0_peer + 8 * sp); }
              rel = true;
            }
            mbar_wait(full0 + 8 * s, (it / K3_NST) & 1);
          }
#pragma unroll
          for (int hf = 0; hf < 2; hf++) {
#pragma unroll
            for (int ks = 2 * hf; ks < 2 * hf + 2; ks++)
              ldsm_x4(a_off + kc * 16384 + ks * 4096, af[ks][0], af[ks][1], af[ks][2], af[ks][3]);
#pragma unroll
            for (int ks = 2 * hf; ks < 2 * hf + 2; ks++) {
              af[ks][0] = hsub2_bf16(af[ks][0], m2[0]); af[ks][1] = hsub2_bf16(af[ks][1], m2[1]);
              af[ks][2] = hsub2_bf16(af[ks][2], m2[0]); af[ks][3] = hsub2_bf16(af[ks][3], m2[1]);
            }
            if (hf == 1 && p == 1 && (kc == 3 || kc == 6) && lane == 0) mbar_arrive(bars + 8 * (B_A3F + (kc == 6)));
            wgmma_fence();
#pragma unroll
            for (int ks = 2 * hf; ks < 2 * hf + 2; ks++) {
              uint64_t dg = make_desc(wst + s * K3_STAGE + ks * 2048, 8192, 1024);
              uint64_t du = make_desc(wst + s * K3_STAGE + 16384 + ks * 2048, 8192, 1024);
              wgmma_rs_n112<1>(ag, af[ks], dg, (kc | ks) != 0);
              wgmma_rs_n112<1>(au, af[ks], du, (kc | ks) != 0);
            }
            wgmma_commit();
            wgmma_wait<1>();
            if (hf == 0 && !rel && tid_wg == 0) { mbar_arrive(empty0 + 8 * sp); mbar_arrive_cluster(empty0_peer + 8 * sp); }
          }
        }
        wgmma_wait<0>();
        if (tid_wg == 0) {
          if (p == 0) { mbar_arrive(empty0 + 8 * (7 % K3_NST)); mbar_arrive_cluster(empty0_peer + 8 * (7 % K3_NST)); }
          else mbar_arrive(bars + 8 * B_P3MAIN);
        }
        if (tid == 0) DBG(3, 3 + 2 * p);
        if (p == 1) named_bar_sync(2, 256);
        bf16* ap = (p == 0 ? g_act + (size_t)(rb * 224 + hs * 28) * 1024 : reinterpret_cast<bf16*>(sptr + OFF_AST)) + rl * 8 + 2 * c;
#pragma unroll
        for (int j = 0; j < 14; j++) {
#pragma unroll
          for (int hh = 0; hh < 2; hh++) {
            uint32_t gp = pack_bf16(ag[4 * j + 2 * hh] * ri[hh], ag[4 * j + 2 * hh + 1] * ri[hh]);
            uint32_t up = pack_bf16(au[4 * j + 2 * hh] * ri[hh], au[4 * j + 2 * hh + 1] * ri[hh]);
            uint32_t sp = pack_bf16(silu_f(bf_lo(gp)), silu_f(bf_hi(gp)));
            *reinterpret_cast<uint32_t*>(ap + j * 1024 + hh * 64) = hmul2_bf16(sp, up);
          }
        }
        if (p == 1) fence_proxy_async();
        mbar_arrive(bars + 8 * (B_ACT0 + p));
        if (tid == 0) DBG(3, 4 + 2 * p);
      }
    }
    {
      const int rb = rbB, kh = cr, nb = (b >> 1) & 3;
      const uint32_t full0 = bars + 8 * B_FULL4, empty0 = bars + 8 * B_EMPTY4, st0 = sbase + OFF_ST4;
      mbar_wait(bars + 8 * B_H4, 0);
      uint32_t hr[16];
#pragma unroll
      for (int j = 0; j < 8; j++)
#pragma unroll
        for (int hh = 0; hh < 2; hh++)
          hr[2 * j + hh] = __ldcg(reinterpret_cast<const uint32_t*>(g_h + ((size_t)(rb * 64 + nb * 16 + kh * 8 + j) * 128 + rl + 8 * hh) * 8 + 2 * c));
      float acc[64];
#pragma unroll 1
      for (int it = 0; it < 8; it++) {
        int s = it % K4_NST, sp = (it + K4_NST - 1) % K4_NST;
        bool rel = (it == 0) || (it - 1 >= 8 - K4_NST);
        if (!mbar_try(full0 + 8 * s, (it / K4_NST) & 1)) {
          if (!rel) {
            wgmma_wait<0>();
            if (tid_wg == 0) mbar_arrive(empty0 + 8 * sp);
            rel = true;
          }
          mbar_wait(full0 + 8 * s, (it / K4_NST) & 1);
        }
        wgmma_fence();
#pragma unroll
        for (int ks = 0; ks < 7; ks++) {
          uint64_t da = make_desc_ns(st0 + s * K4_STAGE + ks * 4096 + wg * 1024, 2048, 128);
          uint64_t db = make_desc(st0 + s * K4_STAGE + 28672 + ks * 2048, 14336, 1024);
          wgmma_n128<0, 1>(acc, da, db, (it | ks) != 0);
        }
        wgmma_commit();
        wgmma_wait<1>();
        if (!rel && tid_wg == 0) mbar_arrive(empty0 + 8 * sp);
      }
      wgmma_wait<0>();
      if (tid == 0) DBG(4, 2);
      mbar_wait(bars + 8 * B_RDY4, 0);
      uint32_t peer_red = mapa(sbase + OFF_RED, kh ^ 1), peer_bar = bars_peer + 8 * B_X4;
#pragma unroll
      for (int j = 0; j < 8; j++) {
        float a0, a1, a2, a3;
        if (kh == 0) { a0 = acc[4 * (8 + j)]; a1 = acc[4 * (8 + j) + 1]; a2 = acc[4 * (8 + j) + 2]; a3 = acc[4 * (8 + j) + 3]; }
        else { a0 = acc[4 * j]; a1 = acc[4 * j + 1]; a2 = acc[4 * j + 2]; a3 = acc[4 * j + 3]; }
        asm volatile("st.async.shared::cluster.mbarrier::complete_tx::bytes.v4.f32 [%0], {%1,%2,%3,%4}, [%5];" ::"r"(peer_red + (j * 256 + tid) * 16),
                     "f"(a0), "f"(a1), "f"(a2), "f"(a3), "r"(peer_bar) : "memory");
      }
      named_bar_sync(2, 256);
      mbar_wait_cluster(bars + 8 * B_X4, 0);
      if (tid == 0) DBG(4, 3);
      uint32_t o[16];
#pragma unroll
      for (int j = 0; j < 8; j++) {
        float4 r = *reinterpret_cast<const float4*>(sptr + OFF_RED + (j * 256 + tid) * 16);
        float a0, a1, a2, a3;
        if (kh == 0) { a0 = acc[4 * j]; a1 = acc[4 * j + 1]; a2 = acc[4 * j + 2]; a3 = acc[4 * j + 3]; }
        else { a0 = acc[4 * (8 + j)]; a1 = acc[4 * (8 + j) + 1]; a2 = acc[4 * (8 + j) + 2]; a3 = acc[4 * (8 + j) + 3]; }
        o[2 * j] = hadd2_bf16(hr[2 * j], pack_bf16(a0 + r.x, a1 + r.y));
        o[2 * j + 1] = hadd2_bf16(hr[2 * j + 1], pack_bf16(a2 + r.z, a3 + r.w));
      }
#pragma unroll
      for (int j = 0; j < 8; j += 2) {
        int row = wg * 64 + w4 * 16 + (lane & 7) + ((lane >> 3) & 1) * 8;
        int grp = j + (lane >> 4);
        uint32_t addr = st0 + row * 128 + ((grp ^ (row & 7)) << 4);
        asm volatile("stmatrix.sync.aligned.m8n8.x4.shared.b16 [%0], {%1,%2,%3,%4};" ::"r"(addr), "r"(o[2 * j]), "r"(o[2 * j + 1]), "r"(o[2 * j + 2]), "r"(o[2 * j + 3]) : "memory");
      }
      fence_proxy_async();
      named_bar_sync(3 + wg, 128);
      if (tid_wg == 0) {
        asm volatile("cp.async.bulk.tensor.2d.global.shared::cta.bulk_group [%0, {%2, %3}], [%1];" ::"l"(&tm_out), "r"(st0 + wg * 8192),
                     "r"(nb * 128 + kh * 64), "r"(rb * 128 + wg * 64) : "memory");
        asm volatile("cp.async.bulk.commit_group;" ::: "memory");
        asm volatile("cp.async.bulk.wait_group.read 0;" ::: "memory");
      }
      if (tid == 0) {
        DBG(4, 4);
        unsigned d = atomicAdd(&g_done, 1);
        if ((d & 127) == 127) atomicAdd(&g_epoch, 1);
      }
    }
    __syncwarp();
    cluster_arrive_relaxed();
    cluster_wait();
  }
}

namespace fb {
constexpr int K1_GRP = 144 * 16 + 64;
constexpr int K1_ACT_BYTES = 64 * K1_GRP;
constexpr int K1_STAGE = 3 * 8192;
constexpr int K1_NST = 3;
constexpr int K1_SMEM = K1_ACT_BYTES + K1_NST * K1_STAGE + 64 + 144 * 4 + 1024;
constexpr int K1_PITCH = 144;

template <int N, typename F>
__device__ __forceinline__ void k1_mainloop_store(F mma, uint32_t act, uint32_t wst, uint32_t full0, uint32_t empty0, uint32_t empty0_peer, int wg, int tid_wg,
                                                  uint32_t stg, const float* rinv) {
  float acc[N / 2];
  uint32_t a_off;
  {
    int l = tid_wg & 31, w4 = tid_wg >> 5;
    int k = (l >> 4) * 8 + (l & 7), mg = 2 * w4 + ((l >> 3) & 1);
    a_off = wg * 8192 + k * 128 + ((mg ^ (k & 7)) << 4);
  }
  uint32_t af[4][4];
#pragma unroll 1
  for (int kc = 0; kc < 8; kc++) {
    const int s = kc % K1_NST, sp = (kc + K1_NST - 1) % K1_NST;
    bool rel = (kc == 0) || (kc - 1 >= 8 - K1_NST);
    if (!mbar_try(full0 + 8 * s, (kc / K1_NST) & 1)) {
      if (!rel) {
        wgmma_wait<0>();
        if (tid_wg == 0) { mbar_arrive(empty0 + 8 * sp); mbar_arrive_cluster(empty0_peer + 8 * sp); }
        rel = true;
      }
      mbar_wait(full0 + 8 * s, (kc / K1_NST) & 1);
    }
#pragma unroll
    for (int hf = 0; hf < 2; hf++) {
#pragma unroll
      for (int ks = 2 * hf; ks < 2 * hf + 2; ks++)
        ldsm_x4_t(wst + s * K1_STAGE + a_off + ks * 2048, af[ks][0], af[ks][1], af[ks][2], af[ks][3]);
      wgmma_fence();
#pragma unroll
      for (int ks = 2 * hf; ks < 2 * hf + 2; ks++) {
        uint64_t db = make_desc_ns(act + (kc * 8 + ks * 2) * K1_GRP, K1_GRP, 128);
        mma(acc, af[ks], db, (kc | ks) != 0);
      }
      wgmma_commit();
      wgmma_wait<1>();
      if (hf == 0 && !rel && tid_wg == 0) { mbar_arrive(empty0 + 8 * sp); mbar_arrive_cluster(empty0_peer + 8 * sp); }
    }
  }
  wgmma_wait<0>();
  named_bar_sync(1, 384);
  int lane = tid_wg & 31, w4 = tid_wg >> 5, c = lane & 3;
#pragma unroll
  for (int j = 0; j < N / 8; j += 2) {
    float2 ra = *reinterpret_cast<const float2*>(rinv + 8 * j + 2 * c);
    float2 rb = *reinterpret_cast<const float2*>(rinv + 8 * j + 8 + 2 * c);
    uint32_t r0 = pack_bf16(acc[4 * j + 0] * ra.x, acc[4 * j + 1] * ra.y);
    uint32_t r1 = pack_bf16(acc[4 * j + 2] * ra.x, acc[4 * j + 3] * ra.y);
    uint32_t r2 = pack_bf16(acc[4 * j + 4] * rb.x, acc[4 * j + 5] * rb.y);
    uint32_t r3 = pack_bf16(acc[4 * j + 6] * rb.x, acc[4 * j + 7] * rb.y);
    int tok = 8 * (j + (lane >> 4)) + (lane & 7);
    uint32_t addr = stg + tok * K1_PITCH + (16 * w4 + 8 * ((lane >> 3) & 1)) * 2;
    asm volatile("stmatrix.sync.aligned.m8n8.x4.trans.shared.b16 [%0], {%1,%2,%3,%4};" ::"r"(addr), "r"(r0), "r"(r1), "r"(r2), "r"(r3) : "memory");
  }
}

__global__ void __launch_bounds__(512, 1) k1_qkv_attn(const __grid_constant__ CUtensorMap tm_wqkv, const bf16* __restrict__ x) {
  extern __shared__ uint8_t smem_raw[];
  uint32_t sbase = (smem_u32(smem_raw) + 1023) & ~1023u;
  uint8_t* sptr = smem_raw + (sbase - smem_u32(smem_raw));
  uint32_t act = sbase, wst = sbase + K1_ACT_BYTES, bars = wst + K1_NST * K1_STAGE;
  uint32_t full0 = bars, empty0 = bars + 8 * K1_NST;
  float* s_rinv = reinterpret_cast<float*>(sptr + K1_ACT_BYTES + K1_NST * K1_STAGE + 64);
  int cr = blockIdx.x & 1, rb = (blockIdx.x >> 4) * 2 + cr, hg = (blockIdx.x >> 1) & 7;
  int tid = threadIdx.x, warp = tid >> 5, lane = tid & 31;
  if (tid == 0) DBG(1, 0);
  uint4 v[3][8];
  if (warp < 12) {
    int gq = lane >> 2, rr = lane & 3;
#pragma unroll
    for (int s = 0; s < 3; s++) {
      int t = rb * 128 - 16 + warp * 12 + s * 4 + rr;
#pragma unroll
      for (int i = 0; i < 8; i++)
        v[s][i] = (t >= 0) ? __ldg(reinterpret_cast<const uint4*>(x + (size_t)t * D_) + 8 * i + gq) : make_uint4(0, 0, 0, 0);
    }
  }
  if (tid == 0) {
    for (int i = 0; i < K1_NST; i++) { mbar_init(full0 + 8 * i, 1); mbar_init(empty0 + 8 * i, 6); }
    fence_barrier_init();
  }
  __syncthreads();
  cluster_arrive();
  pdl_launch_dependents();
  uint32_t empty0_peer = mapa(empty0, cr ^ 1);
  if (warp >= 12) {
    asm volatile("setmaxnreg.dec.sync.aligned.u32 24;");
    cluster_wait();
    if (tid == 384) {
      for (int kc = 0; kc < 8; kc++) {
        int s = kc % K1_NST;
        if (kc >= K1_NST) mbar_wait(empty0 + 8 * s, ((kc / K1_NST) - 1) & 1);
        mbar_expect_tx(full0 + 8 * s, K1_STAGE);
        for (int w = 0; w < 3; w++)
          tma_2d_mc(wst + s * K1_STAGE + w * 8192 + cr * 4096, &tm_wqkv, w * 512 + hg * 64, kc * 64 + cr * 32, full0 + 8 * s, 3);
      }
    }
    __syncwarp();
    cluster_arrive_relaxed();
    cluster_wait();
  } else {
    asm volatile("setmaxnreg.inc.sync.aligned.u32 160;");
    {
      int gq = lane >> 2, rr = lane & 3;
#pragma unroll
      for (int s = 0; s < 3; s++) {
        int r = warp * 12 + s * 4 + rr;
        float ri = ln_set<8>(v[s]);
        if (gq == 0) s_rinv[r] = ri;
#pragma unroll
        for (int i = 0; i < 8; i++) *reinterpret_cast<uint4*>(sptr + (8 * i + gq) * K1_GRP + r * 16) = v[s][i];
      }
    }
    fence_proxy_async();
    cluster_wait();
    named_bar_sync(1, 384);
    if (tid == 0) DBG(1, 1);
    int wg = warp >> 2, tid_wg = tid & 127;
    uint32_t stq = wst, stk = wst + 128 * K1_PITCH, stv = stk + 144 * K1_PITCH;
    if (wg == 0)
      k1_mainloop_store<128>([](float (&d)[64], const uint32_t (&a)[4], uint64_t b, int s) { wgmma_rs_n128<0>(d, a, b, s); }, act + 256, wst, full0,
                             empty0, empty0_peer, wg, tid_wg, stq, s_rinv + 16);
    else
      k1_mainloop_store<144>([](float (&d)[72], const uint32_t (&a)[4], uint64_t b, int s) { wgmma_rs_n144<0>(d, a, b, s); }, act, wst, full0, empty0,
                             empty0_peer, wg, tid_wg, wg == 1 ? stk : stv, s_rinv);
    named_bar_sync(1, 384);
    if (tid == 0) DBG(1, 2);
    {
      bf16* op = g_o + (size_t)(rb * 64 + hg * 8) * 1024;
      if (warp < 8) attn_units<K1_PITCH, 3>(stq, stk, stv, warp, 12, rb * 128, lane, op);
      else attn_units<K1_PITCH, 2>(stq, stk, stv, warp, 12, rb * 128, lane, op);
    }
    if (tid == 0) DBG(1, 3);
    __syncwarp();
    cluster_arrive_relaxed();
    cluster_wait();
  }
}

constexpr int K2_SMEM = 8 * (16384 + 8192) + 64 + 1024;
__global__ void __launch_bounds__(288, 1) k2_wo(const __grid_constant__ CUtensorMap tm_wo, const bf16* __restrict__ x) {
  extern __shared__ uint8_t smem_raw[];
  uint32_t sbase = (smem_u32(smem_raw) + 1023) & ~1023u;
  uint32_t sa = sbase, sb = sbase + 8 * 16384, bars = sb + 8 * 8192;
  int rb = blockIdx.x >> 3, nb = blockIdx.x & 7, cr = blockIdx.x & 1;
  int tid = threadIdx.x, warp = tid >> 5, lane = tid & 31;
  if (tid == 0) DBG(2, 0);
  if (tid == 0) {
    for (int i = 0; i < 8; i++) mbar_init(bars + 8 * i, 1);
    fence_barrier_init();
  }
  __syncthreads();
  cluster_arrive();
  pdl_launch_dependents();
  cluster_wait();
  if (warp == 8) {
    if (lane == 0) {
      for (int kc = 0; kc < 8; kc++) {
        mbar_expect_tx(bars + 8 * kc, 16384 + 8192);
        tma_2d(sb + kc * 8192, &tm_wo, nb * 64, kc * 64, bars + 8 * kc);
      }
      pdl_wait();
      DBG(2, 1);
      for (int kc = 0; kc < 8; kc++)
        bulk_load_mc(sa + kc * 16384 + cr * 8192, g_o + (size_t)(rb * 64 + kc * 8 + cr * 4) * 1024, 8192, bars + 8 * kc, 3);
    }
  } else {
    int wg = warp >> 2, w4 = warp & 3;
    int g = lane >> 2, c = lane & 3;
    int rl = wg * 64 + w4 * 16 + g;
    uint32_t xr[16];
#pragma unroll
    for (int j = 0; j < 8; j++)
#pragma unroll
      for (int hh = 0; hh < 2; hh++)
        xr[2 * j + hh] = __ldg(reinterpret_cast<const uint32_t*>(x + (size_t)(rb * 128 + rl + 8 * hh) * D_ + nb * 64 + 8 * j + 2 * c));
    float acc[32];
#pragma unroll 1
    for (int kc = 0; kc < 8; kc++) {
      mbar_wait(bars + 8 * kc, 0);
      wgmma_fence();
#pragma unroll
      for (int ks = 0; ks < 4; ks++) {
        uint64_t da = make_desc_ns(sa + kc * 16384 + ks * 4096 + wg * 1024, 2048, 128);
        uint64_t db = make_desc(sb + kc * 8192 + ks * 2048, 8192, 1024);
        wgmma_n64<0, 1>(acc, da, db, (kc | ks) != 0);
      }
      wgmma_commit();
    }
    wgmma_wait<0>();
    if (tid == 0) DBG(2, 2);
    float ss[2] = {0.f, 0.f}, qq[2] = {0.f, 0.f};
#pragma unroll
    for (int j = 0; j < 8; j++)
#pragma unroll
      for (int hh = 0; hh < 2; hh++) {
        uint32_t hv = hadd2_bf16(xr[2 * j + hh], pack_bf16(acc[4 * j + 2 * hh], acc[4 * j + 2 * hh + 1]));
        *reinterpret_cast<uint32_t*>(g_h + ((size_t)(rb * 64 + nb * 8 + j) * 128 + rl + 8 * hh) * 8 + 2 * c) = hv;
        float lo = bf_lo(hv), hi = bf_hi(hv);
        ss[hh] += lo + hi;
        qq[hh] = fmaf(lo, lo, fmaf(hi, hi, qq[hh]));
      }
#pragma unroll
    for (int hh = 0; hh < 2; hh++) {
      ss[hh] += __shfl_xor_sync(0xffffffffu, ss[hh], 1); qq[hh] += __shfl_xor_sync(0xffffffffu, qq[hh], 1);
      ss[hh] += __shfl_xor_sync(0xffffffffu, ss[hh], 2); qq[hh] += __shfl_xor_sync(0xffffffffu, qq[hh], 2);
      if (c == 0) g_stats[(rb * 8 + nb) * 128 + rl + 8 * hh] = make_float2(ss[hh], qq[hh]);
    }
    if (tid == 0) DBG(2, 3);
  }
  __syncwarp();
  cluster_arrive_relaxed();
  cluster_wait();
}

constexpr int K3_STAGE = 4 * 8192;
constexpr int K3_NST = 3;
constexpr int K3_SMEM = 8 * 16384 + K3_NST * K3_STAGE + 128 + 1024;
__global__ void __launch_bounds__(384, 1) k3_gateup(const __grid_constant__ CUtensorMap tm_wg, const __grid_constant__ CUtensorMap tm_wu) {
  extern __shared__ uint8_t smem_raw[];
  uint32_t sbase = (smem_u32(smem_raw) + 1023) & ~1023u;
  uint32_t sa = sbase, wst = sbase + 8 * 16384, bars = wst + K3_NST * K3_STAGE;
  uint32_t full0 = bars, empty0 = bars + 8 * K3_NST, afull0 = bars + 16 * K3_NST;
  int cr = blockIdx.x & 1, rb = (blockIdx.x >> 4) * 2 + cr, hs = (blockIdx.x >> 1) & 7;
  int tid = threadIdx.x, warp = tid >> 5, lane = tid & 31;
  if (tid == 0) DBG(3, 0);
  if (tid == 0) {
    for (int i = 0; i < K3_NST; i++) { mbar_init(full0 + 8 * i, 1); mbar_init(empty0 + 8 * i, 4); }
    for (int i = 0; i < 8; i++) mbar_init(afull0 + 8 * i, 1);
    fence_barrier_init();
  }
  __syncthreads();
  cluster_arrive();
  pdl_launch_dependents();
  cluster_wait();
  uint32_t empty0_peer = mapa(empty0, cr ^ 1);
  if (warp >= 8) {
    asm volatile("setmaxnreg.dec.sync.aligned.u32 40;");
    if (tid == 256) {
      const CUtensorMap* tm = cr ? &tm_wu : &tm_wg;
      for (int it = 0; it < 16; it++) {
        int s = it % K3_NST, p = it >> 3, kc = it & 7;
        if (it == K3_NST) {
          pdl_wait();
          for (int k = 0; k < 8; k++) {
            mbar_expect_tx(afull0 + 8 * k, 16384);
            bulk_load(sa + k * 16384, g_h + (size_t)(rb * 64 + k * 8) * 1024, 16384, afull0 + 8 * k);
          }
        }
        if (it >= K3_NST) mbar_wait(empty0 + 8 * s, ((it / K3_NST) - 1) & 1);
        mbar_expect_tx(full0 + 8 * s, K3_STAGE);
        uint32_t d = wst + s * K3_STAGE + cr * 16384;
        tma_3d_mc(d, tm, 0, hs * 2 + p, kc * 64, full0 + 8 * s, 3);
        tma_3d_mc(d + 8192, tm, 64, hs * 2 + p, kc * 64, full0 + 8 * s, 3);
      }
    }
    __syncwarp();
    cluster_arrive_relaxed();
    cluster_wait();
  } else {
    asm volatile("setmaxnreg.inc.sync.aligned.u32 232;");
    int wg = warp >> 2, w4 = warp & 3, tid_wg = tid & 127;
    int g = lane >> 2, c = lane & 3;
    int rl = wg * 64 + w4 * 16 + g;
    pdl_wait();
    if (tid == 0) DBG(3, 1);
    uint32_t m2[2];
    float ri[2];
#pragma unroll
    for (int hh = 0; hh < 2; hh++) {
      float s = 0.f, q = 0.f;
#pragma unroll
      for (int n = 0; n < 8; n++) { float2 t = g_stats[(rb * 8 + n) * 128 + rl + 8 * hh]; s += t.x; q += t.y; }
      ln_finish(s, q, m2[hh], ri[hh]);
    }
    if (tid == 0) DBG(3, 2);
    uint32_t a_off = sa + (lane >> 4) * 2048 + (wg * 64 + w4 * 16 + (lane & 15)) * 16;
#pragma unroll 1
    for (int p = 0; p < 2; p++) {
      float ag[56], au[56];
      uint32_t af[4][4];
#pragma unroll 1
      for (int kc = 0; kc < 8; kc++) {
        int it = p * 8 + kc, s = it % K3_NST, sp = (it + K3_NST - 1) % K3_NST;
        bool rel = (kc == 0) || (it - 1 >= 16 - K3_NST);
        if (p == 0) mbar_wait(afull0 + 8 * kc, 0);
        if (!mbar_try(full0 + 8 * s, (it / K3_NST) & 1)) {
          if (!rel) {
            wgmma_wait<0>();
            if (tid_wg == 0) { mbar_arrive(empty0 + 8 * sp); mbar_arrive_cluster(empty0_peer + 8 * sp); }
            rel = true;
          }
          mbar_wait(full0 + 8 * s, (it / K3_NST) & 1);
        }
#pragma unroll
        for (int hf = 0; hf < 2; hf++) {
#pragma unroll
          for (int ks = 2 * hf; ks < 2 * hf + 2; ks++)
            ldsm_x4(a_off + kc * 16384 + ks * 4096, af[ks][0], af[ks][1], af[ks][2], af[ks][3]);
#pragma unroll
          for (int ks = 2 * hf; ks < 2 * hf + 2; ks++) {
            af[ks][0] = hsub2_bf16(af[ks][0], m2[0]); af[ks][1] = hsub2_bf16(af[ks][1], m2[1]);
            af[ks][2] = hsub2_bf16(af[ks][2], m2[0]); af[ks][3] = hsub2_bf16(af[ks][3], m2[1]);
          }
          wgmma_fence();
#pragma unroll
          for (int ks = 2 * hf; ks < 2 * hf + 2; ks++) {
            uint64_t dg = make_desc(wst + s * K3_STAGE + ks * 2048, 8192, 1024);
            uint64_t du = make_desc(wst + s * K3_STAGE + 16384 + ks * 2048, 8192, 1024);
            wgmma_rs_n112<1>(ag, af[ks], dg, (kc | ks) != 0);
            wgmma_rs_n112<1>(au, af[ks], du, (kc | ks) != 0);
          }
          wgmma_commit();
          wgmma_wait<1>();
          if (hf == 0 && !rel && tid_wg == 0) { mbar_arrive(empty0 + 8 * sp); mbar_arrive_cluster(empty0_peer + 8 * sp); }
        }
      }
      wgmma_wait<0>();
      if (p == 0 && tid_wg == 0) { mbar_arrive(empty0 + 8 * (7 % K3_NST)); mbar_arrive_cluster(empty0_peer + 8 * (7 % K3_NST)); }
      if (tid == 0) DBG(3, 3 + 2 * p);
      bf16* ap = g_act + ((size_t)(rb * 224 + hs * 28 + p * 14) * 128 + rl) * 8 + 2 * c;
#pragma unroll
      for (int j = 0; j < 14; j++) {
#pragma unroll
        for (int hh = 0; hh < 2; hh++) {
          uint32_t gp = pack_bf16(ag[4 * j + 2 * hh] * ri[hh], ag[4 * j + 2 * hh + 1] * ri[hh]);
          uint32_t up = pack_bf16(au[4 * j + 2 * hh] * ri[hh], au[4 * j + 2 * hh + 1] * ri[hh]);
          uint32_t sp = pack_bf16(silu_f(bf_lo(gp)), silu_f(bf_hi(gp)));
          *reinterpret_cast<uint32_t*>(ap + j * 1024 + hh * 64) = hmul2_bf16(sp, up);
        }
      }
      if (tid == 0) DBG(3, 4 + 2 * p);
    }
    __syncwarp();
    cluster_arrive_relaxed();
    cluster_wait();
  }
}

constexpr int K4_STAGE = 32768;
constexpr int K4_NST = 6;
constexpr int K4_SMEM = K4_NST * K4_STAGE + 32768 + 128 + 1024;
__global__ void __launch_bounds__(288, 1)
    k4_down(const __grid_constant__ CUtensorMap tm_wd, const __grid_constant__ CUtensorMap tm_out) {
  extern __shared__ uint8_t smem_raw[];
  uint32_t sbase = (smem_u32(smem_raw) + 1023) & ~1023u;
  uint8_t* sptr = smem_raw + (sbase - smem_u32(smem_raw));
  uint32_t st0 = sbase, red = sbase + K4_NST * K4_STAGE, bars = red + 32768;
  uint32_t full0 = bars, empty0 = bars + 8 * K4_NST, xbar = bars + 16 * K4_NST;
  int kh = blockIdx.x & 1, nb = (blockIdx.x >> 1) & 3, rb = blockIdx.x >> 3;
  int tid = threadIdx.x, warp = tid >> 5, lane = tid & 31;
  if (tid == 0) DBG(4, 0);
  if (tid == 0) {
    for (int i = 0; i < K4_NST; i++) { mbar_init(full0 + 8 * i, 1); mbar_init(empty0 + 8 * i, 2); }
    mbar_init(xbar, 1);
    fence_barrier_init();
    mbar_expect_tx(xbar, 32768);
  }
  __syncthreads();
  cluster_arrive();
  pdl_launch_dependents();
  if (warp == 8) {
    if (lane == 0) {
      const bf16* ap = g_act + (size_t)(rb * 224 + kh * 112) * 1024;
      for (int it = 0; it < K4_NST; it++) {
        mbar_expect_tx(full0 + 8 * it, K4_STAGE);
        uint32_t d = st0 + it * K4_STAGE;
        int k0 = kh * 896 + it * 64;
        tma_2d(d + 16384, &tm_wd, nb * 128, k0, full0 + 8 * it);
        tma_2d(d + 24576, &tm_wd, nb * 128 + 64, k0, full0 + 8 * it);
      }
      pdl_wait();
      DBG(4, 1);
      for (int it = 0; it < K4_NST; it++) bulk_load(st0 + it * K4_STAGE, ap + (size_t)it * 8192, 16384, full0 + 8 * it);
      for (int it = K4_NST; it < 14; it++) {
        int s = it % K4_NST;
        mbar_wait(empty0 + 8 * s, ((it / K4_NST) - 1) & 1);
        mbar_expect_tx(full0 + 8 * s, K4_STAGE);
        uint32_t d = st0 + s * K4_STAGE;
        int k0 = kh * 896 + it * 64;
        tma_2d(d + 16384, &tm_wd, nb * 128, k0, full0 + 8 * s);
        tma_2d(d + 24576, &tm_wd, nb * 128 + 64, k0, full0 + 8 * s);
        bulk_load(d, ap + (size_t)it * 8192, 16384, full0 + 8 * s);
      }
    }
    __syncwarp();
    cluster_wait();
  } else {
    int wg = warp >> 2, w4 = warp & 3, tid_wg = tid & 127;
    int g = lane >> 2, c = lane & 3;
    int rl = wg * 64 + w4 * 16 + g;
    pdl_wait();
    uint32_t hr[16];
#pragma unroll
    for (int j = 0; j < 8; j++)
#pragma unroll
      for (int hh = 0; hh < 2; hh++)
        hr[2 * j + hh] = *reinterpret_cast<const uint32_t*>(g_h + ((size_t)(rb * 64 + nb * 16 + kh * 8 + j) * 128 + rl + 8 * hh) * 8 + 2 * c);
    float acc[64];
#pragma unroll 1
    for (int it = 0; it < 14; it++) {
      int s = it % K4_NST, sp = (it + K4_NST - 1) % K4_NST;
      bool rel = (it == 0) || (it - 1 >= 14 - K4_NST);
      if (!mbar_try(full0 + 8 * s, (it / K4_NST) & 1)) {
        if (!rel) {
          wgmma_wait<0>();
          if (tid_wg == 0) mbar_arrive(empty0 + 8 * sp);
          rel = true;
        }
        mbar_wait(full0 + 8 * s, (it / K4_NST) & 1);
      }
      wgmma_fence();
#pragma unroll
      for (int ks = 0; ks < 4; ks++) {
        uint64_t da = make_desc_ns(st0 + s * K4_STAGE + ks * 4096 + wg * 1024, 2048, 128);
        uint64_t db = make_desc(st0 + s * K4_STAGE + 16384 + ks * 2048, 8192, 1024);
        wgmma_n128<0, 1>(acc, da, db, (it | ks) != 0);
      }
      wgmma_commit();
      wgmma_wait<1>();
      if (!rel && tid_wg == 0) mbar_arrive(empty0 + 8 * sp);
    }
    wgmma_wait<0>();
    if (tid == 0) DBG(4, 2);
    cluster_wait();
    uint32_t peer_red = mapa(red, kh ^ 1), peer_bar = mapa(xbar, kh ^ 1);
#pragma unroll
    for (int j = 0; j < 8; j++) {
      float a0, a1, a2, a3;
      if (kh == 0) { a0 = acc[4 * (8 + j)]; a1 = acc[4 * (8 + j) + 1]; a2 = acc[4 * (8 + j) + 2]; a3 = acc[4 * (8 + j) + 3]; }
      else { a0 = acc[4 * j]; a1 = acc[4 * j + 1]; a2 = acc[4 * j + 2]; a3 = acc[4 * j + 3]; }
      asm volatile("st.async.shared::cluster.mbarrier::complete_tx::bytes.v4.f32 [%0], {%1,%2,%3,%4}, [%5];" ::"r"(peer_red + (j * 256 + tid) * 16),
                   "f"(a0), "f"(a1), "f"(a2), "f"(a3), "r"(peer_bar) : "memory");
    }
    named_bar_sync(1, 256);
    mbar_wait_cluster(xbar, 0);
    if (tid == 0) DBG(4, 3);
    uint32_t o[16];
#pragma unroll
    for (int j = 0; j < 8; j++) {
      float4 r = *reinterpret_cast<const float4*>(sptr + K4_NST * K4_STAGE + (j * 256 + tid) * 16);
      float a0, a1, a2, a3;
      if (kh == 0) { a0 = acc[4 * j]; a1 = acc[4 * j + 1]; a2 = acc[4 * j + 2]; a3 = acc[4 * j + 3]; }
      else { a0 = acc[4 * (8 + j)]; a1 = acc[4 * (8 + j) + 1]; a2 = acc[4 * (8 + j) + 2]; a3 = acc[4 * (8 + j) + 3]; }
      o[2 * j] = hadd2_bf16(hr[2 * j], pack_bf16(a0 + r.x, a1 + r.y));
      o[2 * j + 1] = hadd2_bf16(hr[2 * j + 1], pack_bf16(a2 + r.z, a3 + r.w));
    }
#pragma unroll
    for (int j = 0; j < 8; j += 2) {
      int row = wg * 64 + w4 * 16 + (lane & 7) + ((lane >> 3) & 1) * 8;
      int grp = j + (lane >> 4);
      uint32_t addr = st0 + row * 128 + ((grp ^ (row & 7)) << 4);
      asm volatile("stmatrix.sync.aligned.m8n8.x4.shared.b16 [%0], {%1,%2,%3,%4};" ::"r"(addr), "r"(o[2 * j]), "r"(o[2 * j + 1]), "r"(o[2 * j + 2]), "r"(o[2 * j + 3]) : "memory");
    }
    fence_proxy_async();
    named_bar_sync(2 + wg, 128);
    if (tid_wg == 0) {
      asm volatile("cp.async.bulk.tensor.2d.global.shared::cta.bulk_group [%0, {%2, %3}], [%1];" ::"l"(&tm_out), "r"(st0 + wg * 8192),
                   "r"(nb * 128 + kh * 64), "r"(rb * 128 + wg * 64) : "memory");
      asm volatile("cp.async.bulk.commit_group;" ::: "memory");
      asm volatile("cp.async.bulk.wait_group 0;" ::: "memory");
    }
    if (tid == 0) DBG(4, 4);
  }
}

}

typedef CUresult (*EncFn)(CUtensorMap*, CUtensorMapDataType, cuuint32_t, void*, const cuuint64_t*, const cuuint64_t*, const cuuint32_t*,
                          const cuuint32_t*, CUtensorMapInterleave, CUtensorMapSwizzle, CUtensorMapL2promotion, CUtensorMapFloatOOBfill);

static void enc2d(EncFn enc, CUtensorMap* m, const void* p, uint64_t cols, uint64_t rows, uint32_t bc, uint32_t br) {
  cuuint64_t gd[2] = {cols, rows};
  cuuint64_t gs[1] = {cols * 2};
  cuuint32_t bd[2] = {bc, br};
  cuuint32_t es[2] = {1, 1};
  enc(m, CU_TENSOR_MAP_DATA_TYPE_BFLOAT16, 2, const_cast<void*>(p), gd, gs, bd, es, CU_TENSOR_MAP_INTERLEAVE_NONE, CU_TENSOR_MAP_SWIZZLE_128B,
      CU_TENSOR_MAP_L2_PROMOTION_L2_128B, CU_TENSOR_MAP_FLOAT_OOB_FILL_NONE);
}
static void enc3d_gu(EncFn enc, CUtensorMap* m, const void* p, uint32_t br) {
  cuuint64_t gd[3] = {112, 16, 512};
  cuuint64_t gs[2] = {224, (cuuint64_t)F_ * 2};
  cuuint32_t bd[3] = {64, 1, br};
  cuuint32_t es[3] = {1, 1, 1};
  enc(m, CU_TENSOR_MAP_DATA_TYPE_BFLOAT16, 3, const_cast<void*>(p), gd, gs, bd, es, CU_TENSOR_MAP_INTERLEAVE_NONE, CU_TENSOR_MAP_SWIZZLE_128B,
      CU_TENSOR_MAP_L2_PROMOTION_L2_128B, CU_TENSOR_MAP_FLOAT_OOB_FILL_NONE);
}
template <typename... KArgs, typename... Args>
static void launch_k(void (*kern)(KArgs...), int grid, int block, int smem, int cluster, bool pdl, Args... args) {
  cudaLaunchConfig_t cfg = {};
  cfg.gridDim = dim3(grid); cfg.blockDim = dim3(block); cfg.dynamicSmemBytes = smem; cfg.stream = cudaStreamPerThread;
  cudaLaunchAttribute at[2];
  int n = 0;
  if (cluster > 1) { at[n].id = cudaLaunchAttributeClusterDimension; at[n].val.clusterDim.x = cluster; at[n].val.clusterDim.y = 1; at[n].val.clusterDim.z = 1; n++; }
  if (pdl) { at[n].id = cudaLaunchAttributeProgrammaticStreamSerialization; at[n].val.programmaticStreamSerializationAllowed = 1; n++; }
  cfg.attrs = at; cfg.numAttrs = n;
  cudaLaunchKernelEx(&cfg, kern, args...);
}

extern "C" void kernel_launch(void* const* d_in, const int* in_sizes, int n_in, void* d_out, int out_size) {
  const bf16* x = (const bf16*)d_in[0];
  const bf16* wqkv = (const bf16*)d_in[1];
  const bf16* wo = (const bf16*)d_in[2];
  const bf16* wgate = (const bf16*)d_in[4];
  const bf16* wup = (const bf16*)d_in[5];
  const bf16* wdown = (const bf16*)d_in[6];

  static EncFn enc = nullptr;
  static int use_mega = 1;
  if (!enc) {
    void* fn = nullptr;
    cudaDriverEntryPointQueryResult qr;
    cudaGetDriverEntryPoint("cuTensorMapEncodeTiled", &fn, cudaEnableDefault, &qr);
    enc = (EncFn)fn;
    cudaFuncSetAttribute(mega, cudaFuncAttributeMaxDynamicSharedMemorySize, MK_SMEM);
    cudaFuncSetAttribute(fb::k1_qkv_attn, cudaFuncAttributeMaxDynamicSharedMemorySize, fb::K1_SMEM);
    cudaFuncSetAttribute(fb::k2_wo, cudaFuncAttributeMaxDynamicSharedMemorySize, fb::K2_SMEM);
    cudaFuncSetAttribute(fb::k3_gateup, cudaFuncAttributeMaxDynamicSharedMemorySize, fb::K3_SMEM);
    cudaFuncSetAttribute(fb::k4_down, cudaFuncAttributeMaxDynamicSharedMemorySize, fb::K4_SMEM);
    cudaLaunchConfig_t cfg = {};
    cfg.gridDim = dim3(128); cfg.blockDim = dim3(384); cfg.dynamicSmemBytes = MK_SMEM;
    cudaLaunchAttribute at[1];
    at[0].id = cudaLaunchAttributeClusterDimension; at[0].val.clusterDim.x = 2; at[0].val.clusterDim.y = 1; at[0].val.clusterDim.z = 1;
    cfg.attrs = at; cfg.numAttrs = 1;
    int ncl = 0;
    if (cudaOccupancyMaxActiveClusters(&ncl, mega, &cfg) != cudaSuccess || ncl < 64) use_mega = 0;
    (void)cudaGetLastError();
  }
  CUtensorMap tm_wqkv, tm_wo, tm_wg, tm_wu, tm_wd, tm_out, tm_x;
  enc2d(enc, &tm_x, x, 512, 2048, 64, 144);
  enc2d(enc, &tm_wqkv, wqkv, 1536, 512, 64, 32);
  enc2d(enc, &tm_wo, wo, 512, 512, 64, 64);
  enc3d_gu(enc, &tm_wg, wgate, 64);
  enc3d_gu(enc, &tm_wu, wup, 64);
  enc2d(enc, &tm_wd, wdown, 512, F_, 64, 112);
  enc2d(enc, &tm_out, d_out, 512, 2048, 64, 64);
  if (use_mega) {
    launch_k(mega, 128, 384, MK_SMEM, 2, false, tm_wqkv, tm_wo, tm_wg, tm_wu, tm_wd, tm_out, tm_x, x, wqkv, wo, wgate, wup, wdown);
  } else {
    CUtensorMap tm_wd64;
    enc2d(enc, &tm_wd64, wdown, 512, F_, 64, 64);
    launch_k(fb::k1_qkv_attn, 128, 512, fb::K1_SMEM, 2, false, tm_wqkv, x);
    launch_k(fb::k2_wo, 128, 288, fb::K2_SMEM, 2, true, tm_wo, x);
    launch_k(fb::k3_gateup, 128, 384, fb::K3_SMEM, 2, true, tm_wg, tm_wu);
    launch_k(fb::k4_down, 128, 288, fb::K4_SMEM, 2, true, tm_wd64, tm_out);
  }
}
```
